```python
import torch

def _softmax(x, axis=-1):
    return torch.softmax(x, dim=axis)

def _gelu(x):
    return torch.nn.functional.gelu(x, approximate='tanh')

def _silu(x):
    return torch.nn.functional.silu(x)

def _sigmoid(x):
    return torch.sigmoid(x)

def _layernorm(x, axis=-1, eps=1e-05):
    m = x.mean(dim=axis, keepdim=True)
    v = x.var(dim=axis, keepdim=True, unbiased=False)
    return (x - m) / torch.sqrt(v + eps)

def _scatter_add(tgt, idx, src, axis=0):
    return tgt.clone().index_add_(axis, idx, src)

def _segment_sum(src, seg, n):
    out = torch.zeros((n,) + src.shape[1:], dtype=src.dtype)
    return out.index_add_(0, seg, src)

def _pad(x, pw):
    flat = tuple((v for pair in reversed(pw) for v in pair))
    return torch.nn.functional.pad(x, flat)
kernel_name = 'adaLN_cond__gqa_block_cached__glu_gated_bilinear__decode'

def setup_inputs():

    _w = lambda a: (lambda t: t.to(torch.bfloat16) if t.is_floating_point() else t)(torch.as_tensor(a))

    def _A_setup():
        B, Sq, D = (1, 1, 512)
        Hq, Hkv, Sk, Dh = (32, 32, 4096, 128)
        assert Hq % Hkv == 0, (Hq, Hkv)
        return {'x': _w((lambda *s: torch.randn(*s, dtype=torch.bfloat16) * 0.05)(B, Sq, D)), 'k_cache': _w((lambda *s: torch.randn(*s, dtype=torch.bfloat16) * 0.8)(B, Hkv, Sk, Dh)), 'v_cache': _w((lambda *s: torch.randn(*s, dtype=torch.bfloat16) * 3.2)(B, Hkv, Sk, Dh)), 'wq': _w((lambda *s: torch.randn(*s, dtype=torch.bfloat16) * 0.8)(D, Hq * Dh) * D ** (-0.5)), 'wo': _w((lambda *s: torch.randn(*s, dtype=torch.bfloat16) * 3.2)(Hq * Dh, D) * (Hq * Dh) ** (-0.5))}
    _A_in = _A_setup()

    def _B_setup():
        B, S, D, F = (1, 1, 512, 1376)
        return {'x': _w((lambda *s: torch.randn(*s, dtype=torch.bfloat16) * 0.05)(B, S, D)), 'w_gate': _w((lambda *s: torch.randn(*s, dtype=torch.bfloat16) * 3.2)(D, F) * D ** (-0.5)), 'w_up': _w((lambda *s: torch.randn(*s, dtype=torch.bfloat16) * 3.2)(D, F) * D ** (-0.5)), 'w_down': _w((lambda *s: torch.randn(*s, dtype=torch.bfloat16) * 3.2)(F, D) * F ** (-0.5))}
    _B_in = _B_setup()
    return {'A_x': _A_in['x'], 'A_k_cache': _A_in['k_cache'], 'A_v_cache': _A_in['v_cache'], 'A_wq': _A_in['wq'], 'A_wo': _A_in['wo'], 'B_x': _B_in['x'], 'B_w_gate': _B_in['w_gate'], 'B_w_up': _B_in['w_up'], 'B_w_down': _B_in['w_down'], 'c': _w((lambda *s: torch.randn(*s, dtype=torch.bfloat16) * 0.4)(1, 512) * 8.0), 'w_mod': _w((lambda *s: torch.randn(*s, dtype=torch.bfloat16) * 0.4)(512, 6 * 512) * 512 ** (-0.5) * 8.0)}

def reference(A_x, A_k_cache, A_v_cache, A_wq, A_wo, B_x, B_w_gate, B_w_up, B_w_down, c, w_mod):

    def _A_ref(x, k_cache, v_cache, wq, wo):
        B, Sq, D = x.shape
        Hq, Dh = (32, 128)
        Hkv = k_cache.shape[1]
        rep = Hq // Hkv
        q = (lambda x, *d: x.permute(*d))((x @ wq).reshape(B, Sq, Hq, Dh), 0, 2, 1, 3)
        k = (lambda x, n, axis: torch.repeat_interleave(x, n, dim=axis))(k_cache, rep, axis=1)
        v = (lambda x, n, axis: torch.repeat_interleave(x, n, dim=axis))(v_cache, rep, axis=1)
        scores = torch.einsum('bhqd,bhkd->bhqk', q, k) * Dh ** (-0.5)
        p = _softmax(scores, axis=-1)
        o = torch.einsum('bhqk,bhkd->bhqd', p, v)
        return (lambda x, *d: x.permute(*d))(o, 0, 2, 1, 3).reshape(B, Sq, Hq * Dh) @ wo

    def _B_ref(x, w_gate, w_up, w_down):
        g = torch.einsum('bsd,df->bsf', x, w_gate)
        u = torch.einsum('bsd,df->bsf', x, w_up)
        h = g * u
        return torch.einsum('bsf,fd->bsd', h, w_down)
    x = A_x
    mod = (_silu(c) @ w_mod).reshape(c.shape[0], 6, 1, -1)
    sa, ca, ga, sb, cb, gb = (mod[:, 0].clone(), mod[:, 1].clone(), mod[:, 2].clone(), mod[:, 3].clone(), mod[:, 4].clone(), mod[:, 5].clone())
    h = _layernorm(x, axis=-1) * (1 + ca) + sa
    x = x + ga * _A_ref(h, A_k_cache, A_v_cache, A_wq, A_wo)
    h = _layernorm(x, axis=-1) * (1 + cb) + sb
    x = x + gb * _B_ref(h, B_w_gate, B_w_up, B_w_down)
    return x
```

```cpp
#include <cuda_runtime.h>
#include <cuda.h>
#include <cuda_bf16.h>
#include <stdint.h>

#define NCTA 128
#define NTHREADS 384
#define UNIT_BYTES 16384
#define SLOTS 10
#define U_K 8
#define U_WO 18
#define U_V 32
#define NUNIT 48
#define NFFN 86
#define ZERO_CTA 127
#define SPIN_LIMIT (1 << 18)
#define MBAR_LIMIT (1 << 14)
#define TAU 640
#define T_A 2000
#define PFMAX 5
#define GU_DELAY 800
#define GU_PACE 100
#define GU_EARLY 0
#define GU_EARLY_AT 28
#define WD_POS 8
#define GU_PROMO CU_TENSOR_MAP_L2_PROMOTION_L2_128B
#define WMIN 2
#define WMAX 6
#define ZERO_AT 20
#define STAT_AT 37
#define POLL_SLEEP 0
#define POLL_BELOW 110.f
#define MOD_SLEEP 200
static_assert(WMAX <= SLOTS - 4, "a consumer may only wait on a slot whose previous use has landed");

#define SM_RING 0
#define SM_GU (SLOTS * UNIT_BYTES)
#define SM_WD (SM_GU + 32768)
#define SM_RED (SM_WD + 16384)
#define SM_VEC (SM_RED + 4096)
#define SM_ST (SM_VEC + 256)
#define SM_ML (SM_ST + 128)
#define SM_R3 (SM_ML + 16)
#define SM_TV (SM_R3 + 1024)
#define SM_GB (SM_TV + 4096)
#define SM_BAR (SM_GB + 1024)
#define SM_TOTAL (SM_BAR + 8 * (2 * SLOTS + 5))

struct Params {
    CUtensorMap m_mod, m_wq, m_wo, m_wg, m_wu, m_wd;
    const __nv_bfloat16 *x, *k, *v, *wo, *c, *wg, *wu, *wd;
    __nv_bfloat16* out;
    uint32_t zero;
};

__device__ unsigned int g_epoch;
__device__ __align__(1024) unsigned long long g_zflag[4];
__device__ __align__(1024) unsigned long long g_mod[96 * 128];
__device__ __align__(1024) unsigned long long g_stat[32 * 32 * 2];
#define ACC2_OFF (32 * 64)
__device__ __align__(1024) float4 g_acc[2 * 32 * 64];

__device__ __forceinline__ unsigned long long gtime() { unsigned long long t; asm volatile("mov.u64 %0, %globaltimer;" : "=l"(t)); return t; }
__device__ __forceinline__ uint32_t gtime32() { uint32_t t; asm volatile("mov.u32 %0, %globaltimer_lo;" : "=r"(t) :: "memory"); return t; }
#define STAMP(i)
#define STAMPP(i)
#define CK(i)

__device__ __forceinline__ uint32_t smem_u32(const void* p) { return (uint32_t)__cvta_generic_to_shared(p); }
__device__ __forceinline__ void mbar_init(uint32_t bar, uint32_t cnt) { asm volatile("mbarrier.init.shared::cta.b64 [%0], %1;" :: "r"(bar), "r"(cnt) : "memory"); }
__device__ __forceinline__ void mbar_expect_tx(uint32_t bar, uint32_t bytes) { asm volatile("mbarrier.arrive.expect_tx.shared::cta.b64 _, [%0], %1;" :: "r"(bar), "r"(bytes) : "memory"); }
__device__ __forceinline__ void mbar_arrive(uint32_t bar, uint32_t cnt) { asm volatile("mbarrier.arrive.shared::cta.b64 _, [%0], %1;" :: "r"(bar), "r"(cnt) : "memory"); }
__device__ __forceinline__ void mbar_wait(uint32_t bar, uint32_t parity) {
    uint32_t done; int it = 0;
    do {
        asm volatile("{\n.reg .pred p;\nmbarrier.try_wait.parity.shared::cta.b64 p, [%1], %2;\nselp.u32 %0, 1, 0, p;\n}"
                     : "=r"(done) : "r"(bar), "r"(parity) : "memory");
    } while (!done && ++it < MBAR_LIMIT);
}
__device__ __forceinline__ bool mbar_test(uint32_t bar, uint32_t parity) {
    uint32_t done;
    asm volatile("{\n.reg .pred p;\nmbarrier.test_wait.parity.shared::cta.b64 p, [%1], %2;\nselp.u32 %0, 1, 0, p;\n}"
                 : "=r"(done) : "r"(bar), "r"(parity) : "memory");
    return done != 0;
}
__device__ __forceinline__ void bulk_g2s(uint32_t dst, const void* src, uint32_t bytes, uint32_t bar) {
    asm volatile("cp.async.bulk.shared::cluster.global.mbarrier::complete_tx::bytes [%0], [%1], %2, [%3];"
                 :: "r"(dst), "l"(src), "r"(bytes), "r"(bar) : "memory");
}
__device__ __forceinline__ void bulk_pf(const void* src, uint32_t bytes) {
    asm volatile("cp.async.bulk.prefetch.L2.global [%0], %1;" :: "l"(src), "r"(bytes) : "memory");
}
__device__ __forceinline__ void tma2d(uint32_t dst, const CUtensorMap* m, int c0, int c1, uint32_t bar) {
    asm volatile("cp.async.bulk.tensor.2d.shared::cluster.global.mbarrier::complete_tx::bytes [%0], [%1, {%3, %4}], [%2];"
                 :: "r"(dst), "l"(m), "r"(bar), "r"(c0), "r"(c1) : "memory");
}
__device__ __forceinline__ void tma3d(uint32_t dst, const CUtensorMap* m, int c0, int c1, int c2, uint32_t bar) {
    asm volatile("cp.async.bulk.tensor.3d.shared::cluster.global.mbarrier::complete_tx::bytes [%0], [%1, {%3, %4, %5}], [%2];"
                 :: "r"(dst), "l"(m), "r"(bar), "r"(c0), "r"(c1), "r"(c2) : "memory");
}
__device__ __forceinline__ uint32_t ldg32(const void* p) {
    uint32_t r;
    asm volatile("ld.global.nc.L1::no_allocate.u32 %0, [%1];" : "=r"(r) : "l"(p));
    return r;
}
__device__ __forceinline__ uint32_t lds32(uint32_t a) { uint32_t r; asm volatile("ld.shared.u32 %0, [%1];" : "=r"(r) : "r"(a) : "memory"); return r; }
__device__ __forceinline__ float ldsf(uint32_t a) { float r; asm volatile("ld.shared.f32 %0, [%1];" : "=f"(r) : "r"(a) : "memory"); return r; }
__device__ __forceinline__ void lds64(uint32_t& x, uint32_t& y, uint32_t a) {
    asm volatile("ld.shared.v2.u32 {%0,%1}, [%2];" : "=r"(x), "=r"(y) : "r"(a) : "memory");
}
__device__ __forceinline__ uint4 lds128(uint32_t a) {
    uint4 r;
    asm volatile("ld.shared.v4.u32 {%0,%1,%2,%3}, [%4];" : "=r"(r.x), "=r"(r.y), "=r"(r.z), "=r"(r.w) : "r"(a) : "memory");
    return r;
}
__device__ __forceinline__ float4 lds128f(uint32_t a) {
    float4 r;
    asm volatile("ld.shared.v4.f32 {%0,%1,%2,%3}, [%4];" : "=f"(r.x), "=f"(r.y), "=f"(r.z), "=f"(r.w) : "r"(a) : "memory");
    return r;
}
__device__ __forceinline__ void sts16(uint32_t a, uint32_t v) { asm volatile("st.shared.u16 [%0], %1;" :: "r"(a), "h"((unsigned short)v) : "memory"); }
__device__ __forceinline__ void sts32(uint32_t a, uint32_t v) { asm volatile("st.shared.u32 [%0], %1;" :: "r"(a), "r"(v) : "memory"); }
__device__ __forceinline__ void sts64f(uint32_t a, float x, float y) { asm volatile("st.shared.v2.f32 [%0], {%1,%2};" :: "r"(a), "f"(x), "f"(y) : "memory"); }
__device__ __forceinline__ void sts128f(uint32_t a, float x, float y, float z, float w) {
    asm volatile("st.shared.v4.f32 [%0], {%1,%2,%3,%4};" :: "r"(a), "f"(x), "f"(y), "f"(z), "f"(w) : "memory");
}
__device__ __forceinline__ void mma16816(float (&d)[4], uint32_t a0, uint32_t a1, uint32_t a2, uint32_t a3, uint32_t b0, uint32_t b1) {
    asm volatile("mma.sync.aligned.m16n8k16.row.col.f32.bf16.bf16.f32 {%0,%1,%2,%3}, {%4,%5,%6,%7}, {%8,%9}, {%0,%1,%2,%3};"
                 : "+f"(d[0]), "+f"(d[1]), "+f"(d[2]), "+f"(d[3]) : "r"(a0), "r"(a1), "r"(a2), "r"(a3), "r"(b0), "r"(b1));
}
__device__ __forceinline__ void mma_f(float (&d)[4], const uint32_t (&a)[4], uint32_t b0, uint32_t b1) { mma16816(d, a[0], a[1], a[2], a[3], b0, b1); }
__device__ __forceinline__ void ldsm4(uint32_t (&r)[4], uint32_t addr) {
    asm volatile("ldmatrix.sync.aligned.m8n8.x4.shared.b16 {%0,%1,%2,%3}, [%4];" : "=r"(r[0]), "=r"(r[1]), "=r"(r[2]), "=r"(r[3]) : "r"(addr) : "memory");
}
__device__ __forceinline__ void ldsm4t(uint32_t (&r)[4], uint32_t addr) {
    asm volatile("ldmatrix.sync.aligned.m8n8.x4.trans.shared.b16 {%0,%1,%2,%3}, [%4];" : "=r"(r[0]), "=r"(r[1]), "=r"(r[2]), "=r"(r[3]) : "r"(addr) : "memory");
}
__device__ __forceinline__ uint32_t pack_bf16(float lo, float hi) {
    uint32_t r;
    asm("cvt.rn.bf16x2.f32 %0, %1, %2;" : "=r"(r) : "f"(hi), "f"(lo));
    return r;
}
__device__ __forceinline__ float bf_lo(uint32_t w) { return __uint_as_float(w << 16); }
__device__ __forceinline__ float bf_hi(uint32_t w) { return __uint_as_float(w & 0xffff0000u); }
__device__ __forceinline__ float rbf(float x) { return __uint_as_float(pack_bf16(0.f, x)); }
__device__ __forceinline__ uint32_t mul2(uint32_t a, uint32_t b) { uint32_t r; asm("mul.rn.bf16x2 %0, %1, %2;" : "=r"(r) : "r"(a), "r"(b)); return r; }
__device__ __forceinline__ uint32_t add2(uint32_t a, uint32_t b) { uint32_t r; asm("add.rn.bf16x2 %0, %1, %2;" : "=r"(r) : "r"(a), "r"(b)); return r; }
__device__ __forceinline__ uint32_t sub2(uint32_t a, uint32_t b) { uint32_t r; asm("sub.rn.bf16x2 %0, %1, %2;" : "=r"(r) : "r"(a), "r"(b)); return r; }
__device__ __forceinline__ unsigned long long ld_relaxed64(const unsigned long long* p) {
    unsigned long long v;
    asm volatile("ld.relaxed.gpu.global.u64 %0, [%1];" : "=l"(v) : "l"(p) : "memory");
    return v;
}
__device__ __forceinline__ void st_relaxed64(unsigned long long* p, unsigned long long v) {
    asm volatile("st.relaxed.gpu.global.u64 [%0], %1;" :: "l"(p), "l"(v) : "memory");
}
__device__ __forceinline__ float4 ld_relaxed_f4(const float4* p) {
    float4 v;
    asm volatile("ld.relaxed.gpu.global.v4.f32 {%0,%1,%2,%3}, [%4];" : "=f"(v.x), "=f"(v.y), "=f"(v.z), "=f"(v.w) : "l"(p) : "memory");
    return v;
}
__device__ __forceinline__ void red_f4(float4* p, float a, float b, float c, float d) {
    asm volatile("red.relaxed.gpu.global.add.v4.f32 [%0], {%1,%2,%3,%4};" :: "l"(p), "f"(a), "f"(b), "f"(c), "f"(d) : "memory");
}
__device__ __forceinline__ float4 atom_f4(float4* p, float a, float b, float c, float d) {
    float4 v;
    asm volatile("atom.relaxed.gpu.global.add.v4.f32 {%0,%1,%2,%3}, [%4], {%5,%6,%7,%8};"
                 : "=f"(v.x), "=f"(v.y), "=f"(v.z), "=f"(v.w) : "l"(p), "f"(a), "f"(b), "f"(c), "f"(d) : "memory");
    return v;
}
__device__ __forceinline__ void cbar() { asm volatile("bar.sync 2, 256;" ::: "memory"); }
__device__ __forceinline__ unsigned long long* mod_ptr(int i) { return &g_mod[(i >> 4) * 128 + (i & 15)]; }
__device__ __forceinline__ bool has_tag(unsigned long long v, uint32_t tag) { return (uint32_t)(v >> 32) == tag; }

__device__ __forceinline__ void ln_partial(uint32_t w, uint32_t st, int warp, int lane) {
    const float a = bf_lo(w), b = bf_hi(w);
    float s = a + b, m = (a - b) * (a - b) * 0.5f;
#pragma unroll
    for (int o = 1; o <= 16; o <<= 1) {
        const float so = __shfl_xor_sync(0xffffffffu, s, o), mo = __shfl_xor_sync(0xffffffffu, m, o);
        const float d = s - so;
        s += so;
        m = fmaf(d * d, 0.25f / o, m + mo);
    }
    if (lane == 0) sts64f(st + 8 * warp, s, m);
}
__device__ __forceinline__ void ln_final(uint32_t st, uint32_t& mean2, float& inv_den) {
    const float4 q0 = lds128f(st), q1 = lds128f(st + 16), q2 = lds128f(st + 32), q3 = lds128f(st + 48);
    const float av = (((q0.x + q0.z) + (q1.x + q1.z)) + ((q2.x + q2.z) + (q3.x + q3.z))) * 0.125f;
    const float m2 = ((q0.y + q0.w) + (q1.y + q1.w)) + ((q2.y + q2.w) + (q3.y + q3.w));
    const float e0 = q0.x - av, e1 = q0.z - av, e2 = q1.x - av, e3 = q1.z - av;
    const float e4 = q2.x - av, e5 = q2.z - av, e6 = q3.x - av, e7 = q3.z - av;
    const float ee = ((e0 * e0 + e1 * e1) + (e2 * e2 + e3 * e3)) + ((e4 * e4 + e5 * e5) + (e6 * e6 + e7 * e7));
    const float var = rbf(fmaf(ee, 1.0f / 32768.0f, m2 * (1.0f / 512.0f)));
    mean2 = pack_bf16(av * (1.0f / 64.0f), av * (1.0f / 64.0f));
    float sq;
    asm("sqrt.approx.ftz.f32 %0, %1;" : "=f"(sq) : "f"(rbf(var + 1e-5f)));
    asm("rcp.approx.ftz.f32 %0, %1;" : "=f"(inv_den) : "f"(rbf(sq)));
}
__device__ __forceinline__ uint32_t ln_mod(uint32_t w, uint32_t mean2, float inv_den, uint32_t onep, uint32_t shift) {
    const uint32_t d = sub2(w, mean2);
    return add2(mul2(pack_bf16(bf_lo(d) * inv_den, bf_hi(d) * inv_den), onep), shift);
}
__device__ __forceinline__ uint32_t residual(uint32_t xw, uint32_t gate, float a0, float a1) {
    return add2(xw, mul2(gate, pack_bf16(a0, a1)));
}
__device__ __forceinline__ void load_frag_pair(uint32_t (&X)[4], uint32_t (&Y)[4], uint32_t a0, uint32_t a1) {
    lds64(X[0], X[1], a0); lds64(X[2], X[3], a1);
    lds64(Y[0], Y[1], a0 ^ 64); lds64(Y[2], Y[3], a1 ^ 64);
}
#define ONE2 0x3f803f80u

__global__ void __launch_bounds__(NTHREADS, 1) fused_decode_kernel(const __grid_constant__ Params p) {
    extern __shared__ __align__(1024) unsigned char smem[];
    const int tid = threadIdx.x, cta = blockIdx.x;
    uint32_t sb = smem_u32(smem);
    asm volatile("" : "+r"(sb));
    const int warp = tid >> 5, lane = tid & 31, head = cta >> 2;
    const uint32_t bar_full = sb + SM_BAR, bar_empty = bar_full + 8 * SLOTS;
    const uint32_t bar_mod = bar_empty + 8 * SLOTS, bar_gu = bar_mod + 8, bar_aux = bar_mod + 16, bar_wd = bar_mod + 24, bar_go = bar_mod + 32;
    STAMP(0);

    if (warp < 8) {
        asm volatile("setmaxnreg.inc.sync.aligned.u32 232;");
        const int g = lane >> 2, t = lane & 3;
        const uint32_t cw = ldg32(p.c + 2 * tid);
        const uint32_t xw = ldg32(p.x + 2 * tid);
        uint32_t tag;
        asm volatile("ld.relaxed.gpu.global.u32 %0, [%1];" : "=r"(tag) : "l"(&g_epoch) : "memory");
        const uint32_t zero = p.zero;
        if (tid < 16) st_relaxed64(&g_stat[cta * 16 + tid], 0ull);
        else if (tid >= 32 && tid < 44) st_relaxed64(mod_ptr(12 * cta + tid - 32), 0ull);

        const uint32_t selLo = (g & 1) ? 0x1044u : 0x4410u;
        const uint32_t selHi = (g & 1) ? 0x3244u : 0x4432u;
        const uint32_t fo0 = 2 * t * 128 + (((g >> 1) ^ (2 * t)) << 4) + (g & 1) * 8;
        const uint32_t fo1 = (2 * t + 1) * 128 + (((g >> 1) ^ (2 * t + 1)) << 4) + (g & 1) * 8;
        uint32_t W[32][4];
        uint32_t mean2;
        float inv_den;
        tag += 1;
        sts32(sb + SM_TV + 16 * tid, xw);
        ln_partial(xw, sb + SM_ST, warp, lane);
        asm volatile("bar.sync 1, 384;" ::: "memory");
        ln_final(sb + SM_ST, mean2, inv_den);

        {
            const float c0 = bf_lo(cw), c1 = bf_hi(cw);
            const uint32_t sw = pack_bf16(__fdividef(c0, 1.0f + __expf(-c0)), __fdividef(c1, 1.0f + __expf(-c1)));
            const uint32_t a = sb + SM_GU + (64 * warp + (lane & 7) + 8 * (lane >> 4)) * 48 + ((lane >> 3) & 1) * 16;
            const uint32_t a2 = sb + SM_GU + (64 * warp + lane) * 48 + 32;
            float m0[4] = {0.f, 0.f, 0.f, 0.f}, m1[4] = {0.f, 0.f, 0.f, 0.f};
            mbar_wait(bar_mod, 0);
#pragma unroll
            for (int j = 0; j < 4; j += 2) {
                uint32_t f0[4], f1[4], f2[4];
                ldsm4t(f0, a + j * 768); ldsm4t(f1, a + j * 768 + 768); ldsm4t(f2, a2 + j * 768);
                const uint32_t b0 = __shfl_sync(0xffffffffu, sw, 8 * j + t), b1 = __shfl_sync(0xffffffffu, sw, 8 * j + 4 + t);
                const uint32_t b2 = __shfl_sync(0xffffffffu, sw, 8 * j + 8 + t), b3 = __shfl_sync(0xffffffffu, sw, 8 * j + 12 + t);
                mma_f(m0, f0, b0, b1);
                mma16816(m1, f2[0], 0u, f2[1], 0u, b0, b1);
                mma_f(m0, f1, b2, b3);
                mma16816(m1, f2[2], 0u, f2[3], 0u, b2, b3);
            }
            if (t == 0) sts128f(sb + SM_R3 + (warp * 8 + g) * 16, m0[0], m0[2], m1[0], 0.f);
            cbar();
            if (warp == 0) {
                float s = 0.f;
#pragma unroll
                for (int w = 0; w < 8; w++) s += ldsf(sb + SM_R3 + w * 128 + lane * 4);
                const float s2 = __shfl_down_sync(0xffffffffu, s, 4);
                if (t < 3 && !(g & 1))
                    st_relaxed64(mod_ptr(12 * cta + 4 * t + (g >> 1)), ((unsigned long long)tag << 32) | pack_bf16(s, s2));
            }
            STAMP(1);
        }
        {
            mbar_wait(bar_full + 8 * (warp & 4), 0);
            const uint32_t a = sb + SM_RING + (warp >> 2) * 65536 + (warp & 3) * 8192;
            uint32_t dep = 0;
#pragma unroll
            for (int s = 0; s < 16; s++) {
                const uint32_t as = a + (s >> 3) * 32768 + (s & 7) * 1024;
                load_frag_pair(W[2 * s], W[2 * s + 1], as + fo0, as + fo1);
                dep |= W[2 * s][0] | W[2 * s][2] | W[2 * s + 1][0] | W[2 * s + 1][2];
            }
            dep = __reduce_or_sync(0xffffffffu, dep & zero);
            if (lane < 2) mbar_arrive(bar_empty + 8 * ((warp & 4) + 2 * lane + ((warp >> 1) & 1)) + dep, 4);
            STAMP(15);
        }
        {
            unsigned long long va, vc; int it = 0;
            while (true) {
                va = ld_relaxed64(mod_ptr(tid)); vc = ld_relaxed64(mod_ptr(256 + tid));
                if (__all_sync(0xffffffffu, has_tag(va, tag) && has_tag(vc, tag)) || ++it >= SPIN_LIMIT) break;
                __nanosleep(MOD_SLEEP);
            }
            STAMP(2);
            const uint32_t hw = ln_mod(xw, mean2, inv_den, add2(ONE2, (uint32_t)vc), (uint32_t)va);
            float qa[4][4];
#pragma unroll
            for (int i = 0; i < 4; i++) { qa[i][0] = qa[i][1] = qa[i][2] = qa[i][3] = 0.f; }
#pragma unroll
            for (int s = 0; s < 8; s++) {
                const uint32_t w0 = __shfl_sync(0xffffffffu, hw, 4 * s + t);
                const uint32_t b0 = __byte_perm(w0, 0u, selLo), b1 = __byte_perm(w0, 0u, selHi);
                mma_f(qa[0], W[2 * s], b0, b1);
                mma_f(qa[1], W[2 * s + 1], b0, b1);
                mma_f(qa[2], W[2 * s + 16], b0, b1);
                mma_f(qa[3], W[2 * s + 17], b0, b1);
            }
            if (t == 0) {
#pragma unroll
                for (int i = 0; i < 4; i++) sts128f(sb + SM_RED + warp * 512 + i * 128 + g * 16, qa[i][0], qa[i][1], qa[i][2], qa[i][3]);
            }
            cbar();
            if (tid < 128) {
                float s = 0.f;
#pragma unroll
                for (int w = 0; w < 8; w++) s += ldsf(sb + SM_RED + w * 512 + tid * 4);
                sts16(sb + SM_VEC + 2 * tid, pack_bf16(s, 0.f));
            }
            cbar();
            STAMP(3);
        }
        uint32_t pw[8];
#pragma unroll
        for (int i = 0; i < 8; i++) pw[i] = 0u;
        {
            uint32_t qf[16];
#pragma unroll
            for (int j = 0; j < 16; j++) qf[j] = lds32(sb + SM_VEC + ((j ^ g) << 4) + 4 * t);
            const uint32_t lrow = (lane & 7) + 8 * ((lane >> 3) & 1);
            const uint32_t loff = (warp & 3) * 4096 + lrow * 256 + (((lane >> 4) ^ (lane & 7)) << 4);
            int slot = (U_K + (warp >> 2)) % SLOTS, ph = ((U_K + (warp >> 2)) / SLOTS) & 1;
#pragma unroll 1
            for (int n = 0; n < 8; n++) {
                mbar_wait(bar_full + 8 * slot, ph);
                const uint32_t a = sb + SM_RING + slot * UNIT_BYTES + loff;
                float c0[4] = {0.f, 0.f, 0.f, 0.f}, c1[4] = {0.f, 0.f, 0.f, 0.f};
#pragma unroll
                for (int j = 0; j < 8; j += 2) {
                    uint32_t f0[4], f1[4];
                    ldsm4(f0, a ^ (32 * j));
                    ldsm4(f1, a ^ (32 * j + 32));
                    mma_f(c0, f0, qf[2 * j], qf[2 * j + 1]);
                    mma_f(c1, f1, qf[2 * j + 2], qf[2 * j + 3]);
                }
                const float slo = (g & 1) ? c0[1] + c1[1] : c0[0] + c1[0];
                const float shi = (g & 1) ? c0[3] + c1[3] : c0[2] + c1[2];
                uint32_t r = pack_bf16(slo, shi);
                if (lane == 0) mbar_arrive(bar_empty + 8 * slot + (r & zero), 2);
                r = pack_bf16(bf_lo(r) * 0.08838834764831845f, bf_hi(r) * 0.08838834764831845f);
#pragma unroll
                for (int i = 0; i < 7; i++) pw[i] = pw[i + 1];
                pw[7] = r;
                slot += n < 4 ? 2 : 4; if (slot >= SLOTS) { slot -= SLOTS; ph ^= 1; }
                if (n == 4 + (warp >> 1)) {
                    const int u = U_WO + 4 * (warp >> 1) + (warp & 1), ws = u % SLOTS;
                    mbar_wait(bar_full + 8 * ws, (u / SLOTS) & 1);
                    const uint32_t wa = sb + SM_RING + ws * UNIT_BYTES;
                    uint32_t dep = 0;
#pragma unroll
                    for (int s = 0; s < 16; s++) {
                        load_frag_pair(W[2 * s], W[2 * s + 1], wa + s * 1024 + fo0, wa + s * 1024 + fo1);
                        dep |= W[2 * s][0] | W[2 * s][2] | W[2 * s + 1][0] | W[2 * s + 1][2];
                    }
                    dep = __reduce_or_sync(0xffffffffu, dep & zero);
                    if (lane == 0) mbar_arrive(bar_empty + 8 * ws + dep, 8);
                }
            }
            STAMP(4);
        }
        float mw;
        {
            const bool valid = (t == (g >> 1));
            mw = -INFINITY;
#pragma unroll
            for (int i = 0; i < 8; i++) mw = fmaxf(mw, fmaxf(bf_lo(pw[i]), bf_hi(pw[i])));
            if (!valid) mw = -INFINITY;
#pragma unroll
            for (int o = 16; o > 0; o >>= 1) mw = fmaxf(mw, __shfl_xor_sync(0xffffffffu, mw, o));
            float lw = 0.f;
#pragma unroll
            for (int i = 0; i < 8; i++) {
                const float e0 = valid ? __expf(bf_lo(pw[i]) - mw) : 0.f, e1 = valid ? __expf(bf_hi(pw[i]) - mw) : 0.f;
                lw += e0 + e1;
                pw[i] = pack_bf16(e0, e1);
            }
#pragma unroll
            for (int o = 16; o > 0; o >>= 1) lw += __shfl_xor_sync(0xffffffffu, lw, o);
            if (lane < 2)
                st_relaxed64(&g_stat[(cta * 8 + warp) * 2 + lane], ((unsigned long long)tag << 32) | __float_as_uint(lane ? lw : mw));
        }
        float acc[8][4];
#pragma unroll
        for (int i = 0; i < 8; i++) { acc[i][0] = acc[i][1] = acc[i][2] = acc[i][3] = 0.f; }
        float scale = 0.f;
        const int pl = 16 * (t >> 1) + 2 * g + (t & 1);
        float4* redp = &g_acc[(4 * warp + (pl >> 3)) * 64 + (pl & 7)];
        float4* pollp = &g_acc[(tid >> 3) * 64 + (tid & 7)];
        asm volatile("" : "+l"(redp), "+l"(pollp));
        {
            const uint32_t lrow = (lane & 7) + 8 * (lane >> 4);
            const uint32_t loff = (warp & 3) * 4096 + lrow * 256 + ((((lane >> 3) & 1) ^ (lane & 7)) << 4);
            int slot = (U_V + (warp >> 2)) % SLOTS, ph = ((U_V + (warp >> 2)) / SLOTS) & 1;
#pragma unroll 1
            for (int n = 0; n < 8; n++) {
                if (n == 7) {
                    mbar_wait(bar_aux, 0);
                    scale = __expf(mw - ldsf(sb + SM_ML)) * ldsf(sb + SM_ML + 4);
                }
                const uint32_t b0 = __byte_perm(pw[0], 0u, selLo), b1 = __byte_perm(pw[0], 0u, selHi);
#pragma unroll
                for (int i = 0; i < 7; i++) pw[i] = pw[i + 1];
                mbar_wait(bar_full + 8 * slot, ph);
                const uint32_t a = sb + SM_RING + slot * UNIT_BYTES + loff;
                uint32_t dep = 0;
#pragma unroll
                for (int c = 0; c < 8; c++) {
                    uint32_t f[4];
                    ldsm4t(f, a ^ (32 * c));
                    mma_f(acc[c], f, b0, b1);
                    dep |= f[0];
                }
                if (lane == 0) mbar_arrive(bar_empty + 8 * slot + (dep & zero), 2);
                slot += 2; if (slot >= SLOTS) { slot -= SLOTS; ph ^= 1; }
            }
            STAMP(5);
        }
        {
            CK(0);
            float e[8], f[8];
#pragma unroll
            for (int c = 0; c < 8; c++) { e[c] = acc[c][0] + acc[c][3]; f[c] = acc[c][1] + acc[c][2]; }
            float e2[4], f2[4];
#pragma unroll
            for (int c = 0; c < 8; c += 2) {
                e2[c >> 1] = e[c] + __shfl_xor_sync(0xffffffffu, e[c + 1], 1);
                f2[c >> 1] = f[c] + __shfl_xor_sync(0xffffffffu, f[c + 1], 1);
            }
            const float o0 = e2[0] + __shfl_xor_sync(0xffffffffu, e2[1], 2);
            const float o1 = f2[0] + __shfl_xor_sync(0xffffffffu, f2[1], 2);
            const float o2 = e2[2] + __shfl_xor_sync(0xffffffffu, e2[3], 2);
            const float o3 = f2[2] + __shfl_xor_sync(0xffffffffu, f2[3], 2);
            sts128f(sb + SM_RED + tid * 16, o0 * scale, o1 * scale, o2 * scale, o3 * scale);
            CK(1);
            cbar();
            CK(2);
            if (tid < 128) {
                const uint32_t rp = sb + SM_RED + tid * 4;
                const float s = ((ldsf(rp) + ldsf(rp + 512)) + (ldsf(rp + 1024) + ldsf(rp + 1536))) +
                                ((ldsf(rp + 2048) + ldsf(rp + 2560)) + (ldsf(rp + 3072) + ldsf(rp + 3584)));
                const int comp = tid & 3, tt = (tid >> 2) & 3, gg = tid >> 4;
                const int sidx = 8 * (comp >> 1) + 2 * tt + (comp & 1);
                sts16(sb + SM_VEC + 2 * ((gg >> 1) * 32 + 2 * sidx + (gg & 1)), pack_bf16(s, 0.f));
            }
            cbar();
            CK(3);
            uint4 ov[4];
#pragma unroll
            for (int i = 0; i < 4; i++) ov[i] = lds128(sb + SM_VEC + 64 * t + 16 * i);
            const uint32_t* ow = reinterpret_cast<const uint32_t*>(ov);
#pragma unroll
            for (int i = 0; i < 8; i++) { acc[i][0] = acc[i][1] = acc[i][2] = acc[i][3] = 0.f; }
#pragma unroll
            for (int s = 0; s < 16; s++) {
                const uint32_t b0 = __byte_perm(ow[s], 0u, selLo), b1 = __byte_perm(ow[s], 0u, selHi);
                mma_f(acc[2 * (s & 3)], W[2 * s], b0, b1);
                mma_f(acc[2 * (s & 3) + 1], W[2 * s + 1], b0, b1);
            }
            float X[4];
#pragma unroll
            for (int i = 0; i < 4; i++) {
                const float xa = (acc[0][i] + acc[2][i]) + (acc[4][i] + acc[6][i]);
                const float ya = (acc[1][i] + acc[3][i]) + (acc[5][i] + acc[7][i]);
                X[i] = (t & 2) ? ya : xa;
            }
            red_f4(redp, (t & 1) ? X[2] : X[0], (t & 1) ? X[3] : X[1], 1.0f, 0.0f);
            CK(4);
            STAMP(6);
        }
        if (cta < NFFN) {
            const uint4 tv = lds128(sb + SM_TV + 16 * tid);
            const uint32_t gb = lds32(sb + SM_GB + 4 * (32 * warp + pl));
            uint32_t* outp = reinterpret_cast<uint32_t*>(p.out) + 32 * warp + pl;
            asm volatile("" : "+l"(outp));
            uint32_t fg[4][4], fu[4][4], fd[4][4];
            const uint32_t agu = sb + SM_GU + (64 * warp + (lane & 7) + 8 * (lane >> 4)) * 32 + ((((lane >> 3) ^ (lane >> 2)) & 1) << 4);
            const uint32_t ad = sb + SM_WD + warp * 2048;
            bool have_gu = false, have_wd = false;
            CK(5);
            float4 v; int it = 0;
            while (true) {
                v = ld_relaxed_f4(pollp);
                if (!have_gu && mbar_test(bar_gu, 0)) {
#pragma unroll
                    for (int j = 0; j < 4; j++) { ldsm4t(fg[j], agu + j * 512); ldsm4t(fu[j], agu + 16384 + j * 512); }
                    have_gu = true;
                } else if (!have_wd && mbar_test(bar_wd, 0)) {
                    load_frag_pair(fd[0], fd[1], ad + fo0, ad + fo1);
                    load_frag_pair(fd[2], fd[3], ad + 1024 + fo0, ad + 1024 + fo1);
                    have_wd = true;
                }
                if (__all_sync(0xffffffffu, v.z == (float)NCTA) || ++it >= SPIN_LIMIT) break;
                if (POLL_SLEEP > 0 && __shfl_sync(0xffffffffu, v.z, 0) < POLL_BELOW) __nanosleep(POLL_SLEEP);
            }
            CK(6);
            const uint32_t yw = residual(tv.x, tv.y, v.x, v.y);
            STAMP(8);
            ln_partial(yw, sb + SM_ST + 64, warp, lane);
            if (!have_gu) {
                mbar_wait(bar_gu, 0);
#pragma unroll
                for (int j = 0; j < 4; j++) { ldsm4t(fg[j], agu + j * 512); ldsm4t(fu[j], agu + 16384 + j * 512); }
            }
            cbar();
            ln_final(sb + SM_ST + 64, mean2, inv_den);
            CK(7);
            const uint32_t hw = ln_mod(yw, mean2, inv_den, tv.z, tv.w);
            float cg[2][4], cu[2][4];
#pragma unroll
            for (int i = 0; i < 4; i++) { cg[0][i] = cg[1][i] = cu[0][i] = cu[1][i] = 0.f; }
#pragma unroll
            for (int j = 0; j < 4; j++) {
                const uint32_t b0 = __shfl_sync(0xffffffffu, hw, 8 * j + t), b1 = __shfl_sync(0xffffffffu, hw, 8 * j + 4 + t);
                mma_f(cg[j & 1], fg[j], b0, b1);
                mma_f(cu[j & 1], fu[j], b0, b1);
            }
            const uint32_t yp = __shfl_sync(0xffffffffu, yw, pl);
            if (t == 0) sts128f(sb + SM_R3 + (warp * 8 + g) * 16, cg[0][0] + cg[1][0], cg[0][2] + cg[1][2], cu[0][0] + cu[1][0], cu[0][2] + cu[1][2]);
            if (!have_wd) {
                mbar_wait(bar_wd, 0);
                load_frag_pair(fd[0], fd[1], ad + fo0, ad + fo1);
                load_frag_pair(fd[2], fd[3], ad + 1024 + fo0, ad + 1024 + fo1);
            }
            CK(8);
            cbar();
            CK(9);
            const uint32_t rp = sb + SM_R3 + 4 * lane;
            const float s = rbf(((ldsf(rp) + ldsf(rp + 128)) + (ldsf(rp + 256) + ldsf(rp + 384))) +
                                ((ldsf(rp + 512) + ldsf(rp + 640)) + (ldsf(rp + 768) + ldsf(rp + 896))));
            const uint32_t hh = pack_bf16(s * __shfl_xor_sync(0xffffffffu, s, 2), 0.f);
            uint32_t b[4];
#pragma unroll
            for (int i = 0; i < 4; i++) b[i] = __byte_perm(__shfl_sync(0xffffffffu, hh, 8 * t + 4 * (i & 1) + (i >> 1)), 0u, selLo);
            float X[4] = {0.f, 0.f, 0.f, 0.f}, Y[4] = {0.f, 0.f, 0.f, 0.f}, X2[4] = {0.f, 0.f, 0.f, 0.f}, Y2[4] = {0.f, 0.f, 0.f, 0.f};
            mma_f(X, fd[0], b[0], b[1]);
            mma_f(Y, fd[1], b[0], b[1]);
            mma_f(X2, fd[2], b[2], b[3]);
            mma_f(Y2, fd[3], b[2], b[3]);
#pragma unroll
            for (int i = 0; i < 4; i++) { const float xa = X[i] + X2[i], ya = Y[i] + Y2[i]; X[i] = (t & 2) ? ya : xa; }
            const float v0 = (t & 1) ? X[2] : X[0], v1 = (t & 1) ? X[3] : X[1];
            CK(10);
            STAMP(9);
            const float4 old = atom_f4(redp + ACC2_OFF, v0, v1, 1.0f, 0.0f);
            if (old.z == (float)(NFFN - 1)) *outp = residual(yp, gb, old.x + v0, old.y + v1);
            if (cta == 0 && tid == 0) g_epoch = tag;
            CK(11);
            STAMP(10);
        }
    } else {
        asm volatile("setmaxnreg.dec.sync.aligned.u32 40;");
        const uint32_t t_start = gtime32();
        if (tid == 256) {
            mbar_init(bar_mod, 1);
            mbar_init(bar_full, 1);
            mbar_init(bar_full + 8 * 4, 1);
            asm volatile("fence.mbarrier_init.release.cluster;" ::: "memory");
            mbar_expect_tx(bar_mod, 24576);
            tma2d(sb + SM_GU, &p.m_mod, 24 * cta, 0, bar_mod);
            tma2d(sb + SM_GU + 12288, &p.m_mod, 24 * cta, 256, bar_mod);
            mbar_expect_tx(bar_full, 65536);
            tma3d(sb + SM_RING, &p.m_wq, 0, 0, 2 * head, bar_full);
            mbar_expect_tx(bar_full + 8 * 4, 65536);
            tma3d(sb + SM_RING + 65536, &p.m_wq, 0, 256, 2 * head, bar_full + 8 * 4);
            STAMPP(16);
        } else if (tid == 288) {
            mbar_init(bar_full + 8 * U_K, 1);
            asm volatile("fence.mbarrier_init.release.cluster;" ::: "memory");
            mbar_expect_tx(bar_full + 8 * U_K, UNIT_BYTES);
            bulk_g2s(sb + SM_RING + U_K * UNIT_BYTES, (const char*)p.k + (size_t)cta * (16 * UNIT_BYTES), UNIT_BYTES, bar_full + 8 * U_K);
#pragma unroll
            for (int s = 0; s < SLOTS; s++) {
                if (s != 0 && s != 4 && s != U_K) mbar_init(bar_full + 8 * s, 1);
                mbar_init(bar_empty + 8 * s, 8);
            }
            mbar_init(bar_gu, 1); mbar_init(bar_aux, 2); mbar_init(bar_wd, 1); mbar_init(bar_go, 8);
            asm volatile("fence.mbarrier_init.release.cluster;" ::: "memory");
#pragma unroll
            for (int s = 1; s < U_K; s++) if (s != 4) mbar_arrive(bar_full + 8 * s, 1);
        }
        __syncwarp();
        asm volatile("bar.sync 1, 384;" ::: "memory");
        if (warp == 8) {
            if (lane == 0) {
                const char* kb = (const char*)p.k + (size_t)cta * (16 * UNIT_BYTES);
                const char* vb = (const char*)p.v + (size_t)cta * (16 * UNIT_BYTES) - 18 * UNIT_BYTES;
                const char* ob = (const char*)p.wo + (size_t)cta * (2 * UNIT_BYTES) - 4 * UNIT_BYTES;
                constexpr int U0 = U_K + 1;
                uint32_t slot = U0 % SLOTS, ph = ((U0 / SLOTS) & 1) ^ 1;
                uint32_t sa = (U0 - WMAX) % SLOTS, pa = ((U0 - WMAX) / SLOTS) & 1;
                uint32_t sn = (U0 - WMIN) % SLOTS, pn = ((U0 - WMIN) / SLOTS) & 1;
                uint32_t t_base = t_start + T_A;
                mbar_expect_tx(bar_gu, 32768);
                uint32_t now = t_start;
                int pj = 1;
                int j = 1, wo = 0;
#pragma unroll 1
                for (int u = U0; u < NUNIT; u++) {
                    const bool is_wo = (u >= U_WO && u < U_V && !((u - U_WO) & 2));
#pragma unroll 1
                    for (int it = 0; it < SPIN_LIMIT; it++) {
                        const bool calm = u - WMAX < U_K || mbar_test(bar_full + 8 * sa, pa);
                        const bool ok = calm && (u < SLOTS || mbar_test(bar_empty + 8 * slot, ph));
                        if (ok && (is_wo || pj > j)) break;
                        if ((int)(now - (t_base + pj * TAU)) >= 0 || (ok && u - WMIN >= U_K && mbar_test(bar_full + 8 * sn, pn))) {
                            if (ok && pj == j) { pj++; break; }
                            if (calm && pj < j + PFMAX && pj < 34) {
                                bulk_pf((pj < 4 ? kb : (pj < 6 ? ob : (pj < 18 ? kb - 2 * UNIT_BYTES : vb))) + (size_t)pj * UNIT_BYTES, UNIT_BYTES);
                                pj++;
                                continue;
                            }
                        }
                        now = gtime32();
                    }
                    if (u >= GU_EARLY_AT && u < GU_EARLY_AT + GU_EARLY) {
                        const int i = u - GU_EARLY_AT, r = ((i >> 1) + cta) & 7;
                        if (cta < NFFN) tma2d(sb + SM_GU + (i & 1) * 16384 + r * 2048, (i & 1) ? &p.m_wu : &p.m_wg, 16 * cta, 64 * r, bar_gu);
                        t_base += TAU / 12;
                    }
                    const uint32_t dst = sb + SM_RING + slot * UNIT_BYTES, bar = bar_full + 8 * slot;
                    mbar_expect_tx(bar, UNIT_BYTES);
                    if (is_wo) { tma3d(dst, &p.m_wo, 0, head * 128, wo, bar); wo++; }
                    else {
                        bulk_g2s(dst, (j < 4 ? kb : (j < 18 ? kb - 2 * UNIT_BYTES : vb)) + (size_t)j * UNIT_BYTES, UNIT_BYTES, bar);
                        j += (j == 3) ? 3 : 1;
                    }
                    if (++slot == SLOTS) { slot = 0; ph ^= 1; }
                    if (++sa == SLOTS) { sa = 0; pa ^= 1; }
                    if (++sn == SLOTS) { sn = 0; pn ^= 1; }
                }
                if (cta < NFFN) {
                    mbar_expect_tx(bar_wd, 16384);
                    uint32_t due = t_base + (uint32_t)(34 * TAU + GU_DELAY);
#pragma unroll 1
                    for (int i = GU_EARLY; i <= 16; i++) {
#pragma unroll 1
                        for (int it = 0; it < SPIN_LIMIT; it++) if ((int)(gtime32() - due) >= 0) break;
                        due += GU_PACE;
                        if (i == WD_POS) tma3d(sb + SM_WD, &p.m_wd, 0, 16 * cta, 0, bar_wd);
                        const int r = ((i >> 1) + cta) & 7;
                        if (i < 16) tma2d(sb + SM_GU + (i & 1) * 16384 + r * 2048, (i & 1) ? &p.m_wu : &p.m_wg, 16 * cta, 64 * r, bar_gu);
                    }
                }
                STAMPP(12);
            }
        } else {
            uint32_t tag;
            asm volatile("ld.relaxed.gpu.global.u32 %0, [%1];" : "=r"(tag) : "l"(&g_epoch) : "memory");
            tag += 1;
            if (warp == 9) {
                if (lane == 0) {
                    asm volatile("prefetch.tensormap [%0];" :: "l"(&p.m_wo) : "memory");
                    asm volatile("prefetch.tensormap [%0];" :: "l"(&p.m_wg) : "memory");
                    asm volatile("prefetch.tensormap [%0];" :: "l"(&p.m_wu) : "memory");
                    asm volatile("prefetch.tensormap [%0];" :: "l"(&p.m_wd) : "memory");
                }
                if (cta == ZERO_CTA) {
                    if (lane < 4) st_relaxed64(&g_zflag[lane], 0ull);
#pragma unroll 1
                    for (int i = 0; i <= ZERO_AT / SLOTS; i++) mbar_wait(bar_full + 8 * (ZERO_AT % SLOTS), i & 1);
#pragma unroll 1
                    for (int i = 0; i < 16; i++) g_acc[(4 * i + (lane >> 3)) * 64 + (lane & 7)] = make_float4(0.f, 0.f, 0.f, 0.f);
                    asm volatile("fence.acq_rel.gpu;" ::: "memory");
                    __syncwarp();
                    if (lane == 0) st_relaxed64(g_zflag, (unsigned long long)tag << 32);
                }
            } else if (warp == 10) {
                if (cta < NFFN) {
                    mbar_wait(bar_empty + 8 * (U_K % SLOTS), 0);
#pragma unroll 1
                    for (int i = lane; i < 256; i += 32) {
                        unsigned long long q0, q1, q2, q3; int it = 0;
                        do {
                            q0 = ld_relaxed64(mod_ptr(512 + i)); q1 = ld_relaxed64(mod_ptr(768 + i));
                            q2 = ld_relaxed64(mod_ptr(1024 + i)); q3 = ld_relaxed64(mod_ptr(1280 + i));
                        } while (!(has_tag(q0, tag) && has_tag(q1, tag) && has_tag(q2, tag) && has_tag(q3, tag)) && ++it < SPIN_LIMIT);
                        sts32(sb + SM_TV + 16 * i + 4, (uint32_t)q0);
                        sts32(sb + SM_TV + 16 * i + 8, add2(ONE2, (uint32_t)q2));
                        sts32(sb + SM_TV + 16 * i + 12, (uint32_t)q1);
                        sts32(sb + SM_GB + 4 * i, (uint32_t)q3);
                    }
                }
                __syncwarp();
                if (lane == 0) mbar_arrive(bar_aux, 1);
            } else {
#pragma unroll 1
                for (int i = 0; i <= STAT_AT / SLOTS; i++) mbar_wait(bar_empty + 8 * (STAT_AT % SLOTS), i & 1);
                const unsigned long long* sp = &g_stat[(head * 32 + lane) * 2];
                unsigned long long q0, q1, q2; int it = 0;
                while (true) {
                    q0 = ld_relaxed64(sp); q1 = ld_relaxed64(sp + 1);
                    asm volatile("ld.acquire.gpu.global.u64 %0, [%1];" : "=l"(q2) : "l"(g_zflag) : "memory");
                    if (__all_sync(0xffffffffu, has_tag(q0, tag) && has_tag(q1, tag) && has_tag(q2, tag)) || ++it >= SPIN_LIMIT) break;
                    __nanosleep(500);
                }
                const float mi = __uint_as_float((uint32_t)q0);
                float m = mi;
#pragma unroll
                for (int o = 16; o > 0; o >>= 1) m = fmaxf(m, __shfl_xor_sync(0xffffffffu, m, o));
                float l = __uint_as_float((uint32_t)q1) * __expf(mi - m);
#pragma unroll
                for (int o = 16; o > 0; o >>= 1) l += __shfl_xor_sync(0xffffffffu, l, o);
                if (lane == 0) {
                    sts64f(sb + SM_ML, m, __fdividef(1.0f, l));
                    mbar_arrive(bar_aux, 1);
                }
            }
        }
    }
}

typedef CUresult (*EncodeFn)(CUtensorMap*, CUtensorMapDataType, cuuint32_t, void*, const cuuint64_t*, const cuuint64_t*,
                             const cuuint32_t*, const cuuint32_t*, CUtensorMapInterleave, CUtensorMapSwizzle,
                             CUtensorMapL2promotion, CUtensorMapFloatOOBfill);
static void encode2d(EncodeFn f, CUtensorMap* m, const void* ptr, int cols, int rows, int bc, int br, CUtensorMapSwizzle sw, CUtensorMapL2promotion pr) {
    cuuint64_t dim[2] = {(cuuint64_t)cols, (cuuint64_t)rows};
    cuuint64_t str[1] = {(cuuint64_t)cols * 2};
    cuuint32_t box[2] = {(cuuint32_t)bc, (cuuint32_t)br};
    cuuint32_t es[2] = {1, 1};
    f(m, CU_TENSOR_MAP_DATA_TYPE_BFLOAT16, 2, (void*)ptr, dim, str, box, es, CU_TENSOR_MAP_INTERLEAVE_NONE, sw,
      pr, CU_TENSOR_MAP_FLOAT_OOB_FILL_NONE);
}
static void encode3d(EncodeFn f, CUtensorMap* m, const void* ptr, int cols, int rows, int br, int bb) {
    cuuint64_t dim[3] = {64, (cuuint64_t)rows, (cuuint64_t)(cols / 64)};
    cuuint64_t str[2] = {(cuuint64_t)cols * 2, 128};
    cuuint32_t box[3] = {64, (cuuint32_t)br, (cuuint32_t)bb};
    cuuint32_t es[3] = {1, 1, 1};
    f(m, CU_TENSOR_MAP_DATA_TYPE_BFLOAT16, 3, (void*)ptr, dim, str, box, es, CU_TENSOR_MAP_INTERLEAVE_NONE, CU_TENSOR_MAP_SWIZZLE_128B,
      CU_TENSOR_MAP_L2_PROMOTION_L2_128B, CU_TENSOR_MAP_FLOAT_OOB_FILL_NONE);
}

extern "C" void kernel_launch(void* const* d_in, const int* in_sizes, int n_in, void* d_out, int out_size) {
    Params p;
    void* fn = nullptr;
    cudaDriverEntryPointQueryResult qr;
    cudaGetDriverEntryPoint("cuTensorMapEncodeTiled", &fn, cudaEnableDefault, &qr);
    EncodeFn enc = (EncodeFn)fn;
    encode2d(enc, &p.m_mod, d_in[10], 3072, 512, 24, 256, CU_TENSOR_MAP_SWIZZLE_NONE, CU_TENSOR_MAP_L2_PROMOTION_L2_128B);
    encode3d(enc, &p.m_wq, d_in[3], 4096, 512, 256, 2);
    encode3d(enc, &p.m_wo, d_in[4], 512, 4096, 128, 1);
    encode3d(enc, &p.m_wd, d_in[8], 512, 1376, 16, 8);
    encode2d(enc, &p.m_wg, d_in[6], 1376, 512, 16, 64, CU_TENSOR_MAP_SWIZZLE_32B, GU_PROMO);
    encode2d(enc, &p.m_wu, d_in[7], 1376, 512, 16, 64, CU_TENSOR_MAP_SWIZZLE_32B, GU_PROMO);
    p.x = (const __nv_bfloat16*)d_in[0];
    p.k = (const __nv_bfloat16*)d_in[1];
    p.v = (const __nv_bfloat16*)d_in[2];
    p.wg = (const __nv_bfloat16*)d_in[6];
    p.wu = (const __nv_bfloat16*)d_in[7];
    p.wd = (const __nv_bfloat16*)d_in[8];
    p.wo = (const __nv_bfloat16*)d_in[4];
    p.c = (const __nv_bfloat16*)d_in[9];
    p.out = (__nv_bfloat16*)d_out;
    p.zero = 0;
    cudaFuncSetAttribute(fused_decode_kernel, cudaFuncAttributeMaxDynamicSharedMemorySize, SM_TOTAL);
    fused_decode_kernel<<<NCTA, NTHREADS, SM_TOTAL>>>(p);
}
```

```cpp
#include <cuda_runtime.h>
#include <cuda.h>
#include <cuda_bf16.h>
#include <stdint.h>

#define NCTA 128
#define NTHREADS 384
#define UNIT_BYTES 16384
#define SLOTS 10
#define U_K 8
#define U_WO 18
#define U_V 32
#define NUNIT 48
#define NFFN 86
#define ZERO_CTA 125
#define SPIN_LIMIT (1 << 18)
#define MBAR_LIMIT (1 << 14)
#define TAU 650
#define T_A 1400
#define PFMAX 5
#define GU_DELAY 300
#define GU_PACE 220
#define WD_LAG 1760
#define GU_UNIT 44
#define GU_FORCE 46
#define WD_PACE 120
#define WMIN 2
#define WMAX 6
#define GU_ROWS 64
#define POLL_K 5
#define MOD_SLEEP 200
static_assert(WMAX <= SLOTS - 4, "a consumer may only wait on a slot whose previous use has landed");

#define SM_RING 0
#define SM_GU (SLOTS * UNIT_BYTES)
#define SM_WD (SM_GU + 32768)
#define SM_RED (SM_WD + 16384)
#define SM_VEC (SM_RED + 4096)
#define SM_ST (SM_VEC + 256)
#define SM_ML (SM_ST + 128)
#define SM_R3 (SM_ML + 16)
#define SM_TV (SM_R3 + 1024)
#define SM_GB (SM_TV + 4096)
#define SM_PL (SM_GB + 1024)
#define SM_BV (SM_PL + 1024)
#define SM_BAR (SM_BV + 4608)
#define SM_TOTAL (SM_BAR + 8 * (2 * SLOTS + 8))

struct Params {
    const __nv_bfloat16 *k, *v, *x, *c, *wo;
    __nv_bfloat16* out;
    uint32_t zero;
    CUtensorMap m_mod, m_wq, m_wo, m_wg, m_wu, m_wd, m_v;
};

__device__ unsigned int g_epoch;
__device__ __align__(1024) unsigned long long g_zflag[4];
__device__ __align__(1024) unsigned long long g_mod[96 * 128];
__device__ __align__(1024) unsigned long long g_stat[32 * 32 * 2];
__device__ __align__(1024) unsigned long long g_ls[NCTA * 64];
#define ACC2_OFF (32 * 64)
__device__ __align__(1024) float4 g_acc[2 * 32 * 64];

__device__ __forceinline__ uint32_t gtime32() { uint32_t t; asm volatile("mov.u32 %0, %globaltimer_lo;" : "=r"(t) :: "memory"); return t; }
__device__ __forceinline__ uint32_t clock32() { uint32_t t; asm volatile("mov.u32 %0, %clock;" : "=r"(t) :: "memory"); return t; }

__device__ __forceinline__ uint32_t smem_u32(const void* p) { return (uint32_t)__cvta_generic_to_shared(p); }
__device__ __forceinline__ void mbar_init(uint32_t bar, uint32_t cnt) { asm volatile("mbarrier.init.shared::cta.b64 [%0], %1;" :: "r"(bar), "r"(cnt) : "memory"); }
__device__ __forceinline__ void mbar_expect_tx(uint32_t bar, uint32_t bytes) { asm volatile("mbarrier.arrive.expect_tx.shared::cta.b64 _, [%0], %1;" :: "r"(bar), "r"(bytes) : "memory"); }
__device__ __forceinline__ void mbar_arrive(uint32_t bar, uint32_t cnt) { asm volatile("mbarrier.arrive.shared::cta.b64 _, [%0], %1;" :: "r"(bar), "r"(cnt) : "memory"); }
__device__ __forceinline__ void mbar_wait(uint32_t bar, uint32_t parity) {
    uint32_t done; int it = 0;
    do {
        asm volatile("{\n.reg .pred p;\nmbarrier.try_wait.parity.shared::cta.b64 p, [%1], %2;\nselp.u32 %0, 1, 0, p;\n}"
                     : "=r"(done) : "r"(bar), "r"(parity) : "memory");
    } while (!done && ++it < MBAR_LIMIT);
}
__device__ __forceinline__ bool mbar_test(uint32_t bar, uint32_t parity) {
    uint32_t done;
    asm volatile("{\n.reg .pred p;\nmbarrier.test_wait.parity.shared::cta.b64 p, [%1], %2;\nselp.u32 %0, 1, 0, p;\n}"
                 : "=r"(done) : "r"(bar), "r"(parity) : "memory");
    return done != 0;
}
__device__ __forceinline__ void bulk_g2s(uint32_t dst, const void* src, uint32_t bytes, uint32_t bar) {
    uint64_t pol;
    asm("createpolicy.fractional.L2::evict_first.b64 %0, 1.0;" : "=l"(pol));
    asm volatile("cp.async.bulk.shared::cluster.global.mbarrier::complete_tx::bytes.L2::cache_hint [%0], [%1], %2, [%3], %4;"
                 :: "r"(dst), "l"(src), "r"(bytes), "r"(bar), "l"(pol) : "memory");
}
__device__ __forceinline__ void bulk_pf(const void* src, uint32_t bytes) {
    asm volatile("cp.async.bulk.prefetch.L2.global [%0], %1;" :: "l"(src), "r"(bytes) : "memory");
}
__device__ __forceinline__ void tma2d(uint32_t dst, const CUtensorMap* m, int c0, int c1, uint32_t bar) {
    asm volatile("cp.async.bulk.tensor.2d.shared::cluster.global.mbarrier::complete_tx::bytes [%0], [%1, {%3, %4}], [%2];"
                 :: "r"(dst), "l"(m), "r"(bar), "r"(c0), "r"(c1) : "memory");
}
__device__ __forceinline__ void tma3d(uint32_t dst, const CUtensorMap* m, int c0, int c1, int c2, uint32_t bar) {
    asm volatile("cp.async.bulk.tensor.3d.shared::cluster.global.mbarrier::complete_tx::bytes [%0], [%1, {%3, %4, %5}], [%2];"
                 :: "r"(dst), "l"(m), "r"(bar), "r"(c0), "r"(c1), "r"(c2) : "memory");
}
__device__ __forceinline__ uint32_t ldg32(const void* p) {
    uint32_t r;
    asm volatile("ld.global.nc.L1::no_allocate.u32 %0, [%1];" : "=r"(r) : "l"(p));
    return r;
}
__device__ __forceinline__ uint32_t lds32(uint32_t a) { uint32_t r; asm volatile("ld.shared.u32 %0, [%1];" : "=r"(r) : "r"(a) : "memory"); return r; }
__device__ __forceinline__ float ldsf(uint32_t a) { float r; asm volatile("ld.shared.f32 %0, [%1];" : "=f"(r) : "r"(a) : "memory"); return r; }
__device__ __forceinline__ void lds64(uint32_t& x, uint32_t& y, uint32_t a) {
    asm volatile("ld.shared.v2.u32 {%0,%1}, [%2];" : "=r"(x), "=r"(y) : "r"(a) : "memory");
}
__device__ __forceinline__ uint4 lds128(uint32_t a) {
    uint4 r;
    asm volatile("ld.shared.v4.u32 {%0,%1,%2,%3}, [%4];" : "=r"(r.x), "=r"(r.y), "=r"(r.z), "=r"(r.w) : "r"(a) : "memory");
    return r;
}
__device__ __forceinline__ float4 lds128f(uint32_t a) {
    float4 r;
    asm volatile("ld.shared.v4.f32 {%0,%1,%2,%3}, [%4];" : "=f"(r.x), "=f"(r.y), "=f"(r.z), "=f"(r.w) : "r"(a) : "memory");
    return r;
}
__device__ __forceinline__ void sts16(uint32_t a, uint32_t v) { asm volatile("st.shared.u16 [%0], %1;" :: "r"(a), "h"((unsigned short)v) : "memory"); }
__device__ __forceinline__ void sts32(uint32_t a, uint32_t v) { asm volatile("st.shared.u32 [%0], %1;" :: "r"(a), "r"(v) : "memory"); }
__device__ __forceinline__ void sts64f(uint32_t a, float x, float y) { asm volatile("st.shared.v2.f32 [%0], {%1,%2};" :: "r"(a), "f"(x), "f"(y) : "memory"); }
__device__ __forceinline__ void sts128f(uint32_t a, float x, float y, float z, float w) {
    asm volatile("st.shared.v4.f32 [%0], {%1,%2,%3,%4};" :: "r"(a), "f"(x), "f"(y), "f"(z), "f"(w) : "memory");
}
__device__ __forceinline__ void mma16816(float (&d)[4], uint32_t a0, uint32_t a1, uint32_t a2, uint32_t a3, uint32_t b0, uint32_t b1) {
    asm volatile("mma.sync.aligned.m16n8k16.row.col.f32.bf16.bf16.f32 {%0,%1,%2,%3}, {%4,%5,%6,%7}, {%8,%9}, {%0,%1,%2,%3};"
                 : "+f"(d[0]), "+f"(d[1]), "+f"(d[2]), "+f"(d[3]) : "r"(a0), "r"(a1), "r"(a2), "r"(a3), "r"(b0), "r"(b1));
}
__device__ __forceinline__ void mma_f(float (&d)[4], const uint32_t (&a)[4], uint32_t b0, uint32_t b1) { mma16816(d, a[0], a[1], a[2], a[3], b0, b1); }
__device__ __forceinline__ void ldsm4(uint32_t (&r)[4], uint32_t addr) {
    asm volatile("ldmatrix.sync.aligned.m8n8.x4.shared.b16 {%0,%1,%2,%3}, [%4];" : "=r"(r[0]), "=r"(r[1]), "=r"(r[2]), "=r"(r[3]) : "r"(addr) : "memory");
}
__device__ __forceinline__ void ldsm4t(uint32_t (&r)[4], uint32_t addr) {
    asm volatile("ldmatrix.sync.aligned.m8n8.x4.trans.shared.b16 {%0,%1,%2,%3}, [%4];" : "=r"(r[0]), "=r"(r[1]), "=r"(r[2]), "=r"(r[3]) : "r"(addr) : "memory");
}
__device__ __forceinline__ uint32_t pack_bf16(float lo, float hi) {
    uint32_t r;
    asm("cvt.rn.bf16x2.f32 %0, %1, %2;" : "=r"(r) : "f"(hi), "f"(lo));
    return r;
}
__device__ __forceinline__ float bf_lo(uint32_t w) { return __uint_as_float(w << 16); }
__device__ __forceinline__ float bf_hi(uint32_t w) { return __uint_as_float(w & 0xffff0000u); }
__device__ __forceinline__ float rbf(float x) { return __uint_as_float(pack_bf16(0.f, x)); }
__device__ __forceinline__ uint32_t mul2(uint32_t a, uint32_t b) { uint32_t r; asm("mul.rn.bf16x2 %0, %1, %2;" : "=r"(r) : "r"(a), "r"(b)); return r; }
__device__ __forceinline__ uint32_t add2(uint32_t a, uint32_t b) { uint32_t r; asm("add.rn.bf16x2 %0, %1, %2;" : "=r"(r) : "r"(a), "r"(b)); return r; }
__device__ __forceinline__ uint32_t sub2(uint32_t a, uint32_t b) { uint32_t r; asm("sub.rn.bf16x2 %0, %1, %2;" : "=r"(r) : "r"(a), "r"(b)); return r; }
__device__ __forceinline__ unsigned long long ld_relaxed64(const unsigned long long* p) {
    unsigned long long v;
    asm volatile("ld.relaxed.gpu.global.u64 %0, [%1];" : "=l"(v) : "l"(p) : "memory");
    return v;
}
__device__ __forceinline__ void st_relaxed64(unsigned long long* p, unsigned long long v) {
    asm volatile("st.relaxed.gpu.global.u64 [%0], %1;" :: "l"(p), "l"(v) : "memory");
}
__device__ __forceinline__ float4 ld_relaxed_f4(const float4* p) {
    float4 v;
    asm volatile("ld.relaxed.gpu.global.v4.f32 {%0,%1,%2,%3}, [%4];" : "=f"(v.x), "=f"(v.y), "=f"(v.z), "=f"(v.w) : "l"(p) : "memory");
    return v;
}
__device__ __forceinline__ void red_f4(float4* p, float a, float b, float c, float d) {
    asm volatile("red.relaxed.gpu.global.add.v4.f32 [%0], {%1,%2,%3,%4};" :: "l"(p), "f"(a), "f"(b), "f"(c), "f"(d) : "memory");
}
__device__ __forceinline__ float4 atom_f4(float4* p, float a, float b, float c, float d) {
    float4 v;
    asm volatile("atom.relaxed.gpu.global.add.v4.f32 {%0,%1,%2,%3}, [%4], {%5,%6,%7,%8};"
                 : "=f"(v.x), "=f"(v.y), "=f"(v.z), "=f"(v.w) : "l"(p), "f"(a), "f"(b), "f"(c), "f"(d) : "memory");
    return v;
}
__device__ __forceinline__ void cbar() { asm volatile("bar.sync 2, 256;" ::: "memory"); }
__device__ __forceinline__ unsigned long long* mod_ptr(int i) { return &g_mod[(i >> 4) * 128 + (i & 15)]; }
__device__ __forceinline__ int acc_idx(int i) { return (i >> 3) * 64 + ((i >> 2) & 1) * 16 + (i & 3); }
__device__ __forceinline__ bool has_tag(unsigned long long v, uint32_t tag) { return (uint32_t)(v >> 32) == tag; }

__device__ __forceinline__ void ln_partial(uint32_t w, uint32_t st, int warp, int lane) {
    const float a = bf_lo(w), b = bf_hi(w);
    float s = a + b, m = (a - b) * (a - b) * 0.5f;
#pragma unroll
    for (int o = 1; o <= 16; o <<= 1) {
        const float so = __shfl_xor_sync(0xffffffffu, s, o), mo = __shfl_xor_sync(0xffffffffu, m, o);
        const float d = s - so;
        s += so;
        m = fmaf(d * d, 0.25f / o, m + mo);
    }
    if (lane == 0) sts64f(st + 8 * warp, s, m);
}
__device__ __forceinline__ void ln_final(const float4& q0, const float4& q1, const float4& q2, const float4& q3, uint32_t& mean2, float& inv_den) {
    const float m2 = ((q0.y + q0.w) + (q1.y + q1.w)) + ((q2.y + q2.w) + (q3.y + q3.w));
    const float e1 = q0.z - q0.x, e2 = q1.x - q0.x, e3 = q1.z - q0.x, e4 = q2.x - q0.x, e5 = q2.z - q0.x, e6 = q3.x - q0.x, e7 = q3.z - q0.x;
    const float t1 = ((e1 + e2) + (e3 + e4)) + ((e5 + e6) + e7);
    const float t2 = (fmaf(e1, e1, e2 * e2) + fmaf(e3, e3, e4 * e4)) + fmaf(e7, e7, fmaf(e5, e5, e6 * e6));
    const float var = rbf(fmaf(fmaf(t1 * -0.125f, t1, t2), 1.0f / 32768.0f, m2 * (1.0f / 512.0f)));
    const float mean = fmaf(t1, 1.0f / 512.0f, q0.x * (1.0f / 64.0f));
    mean2 = pack_bf16(mean, mean);
    const float ve = rbf(var + 1e-5f);
    float rs;
    asm("rsqrt.approx.ftz.f32 %0, %1;" : "=f"(rs) : "f"(ve));
    const float e = fmaf(-rbf(ve * rs), rs, 1.0f);
    inv_den = fmaf(fmaf(e, e, e), rs, rs);
}
__device__ __forceinline__ uint32_t ln_mod(uint32_t w, uint32_t mean2, float inv_den, uint32_t onep, uint32_t shift) {
    const uint32_t d = sub2(w, mean2);
    return add2(mul2(pack_bf16(bf_lo(d) * inv_den, bf_hi(d) * inv_den), onep), shift);
}
__device__ __forceinline__ uint32_t residual(uint32_t xw, uint32_t gate, float a0, float a1) {
    return add2(xw, mul2(gate, pack_bf16(a0, a1)));
}
__device__ __forceinline__ void load_frag_pair(uint32_t (&X)[4], uint32_t (&Y)[4], uint32_t a0, uint32_t a1) {
    lds64(X[0], X[1], a0); lds64(X[2], X[3], a1);
    lds64(Y[0], Y[1], a0 ^ 64); lds64(Y[2], Y[3], a1 ^ 64);
}
#define ONE2 0x3f803f80u

__global__ void __launch_bounds__(NTHREADS, 1) fused_decode_kernel(const __grid_constant__ Params p) {
    extern __shared__ __align__(1024) unsigned char smem[];
    const int tid = threadIdx.x, cta = blockIdx.x;
    uint32_t sb = smem_u32(smem);
    asm volatile("" : "+r"(sb));
    const int warp = tid >> 5, lane = tid & 31, head = cta >> 2;
    const int ffn = cta - cta / 3;
    const bool is_ffn = cta % 3 != 2;
    const uint32_t bar_full = sb + SM_BAR, bar_empty = bar_full + 8 * SLOTS;
    const uint32_t bar_mod = bar_empty + 8 * SLOTS, bar_gu = bar_mod + 8, bar_aux = bar_mod + 16, bar_wd = bar_mod + 24, bar_go = bar_mod + 32;
    const uint32_t bar_trig = bar_mod + 40;

    if (warp < 8) {
        asm volatile("setmaxnreg.inc.sync.aligned.u32 232;");
        const int g = lane >> 2, t = lane & 3;
        const uint32_t cw = ldg32(p.c + 2 * tid);
        const uint32_t xw = ldg32(p.x + 2 * tid);
        uint32_t tag;
        asm volatile("ld.relaxed.gpu.global.u32 %0, [%1];" : "=r"(tag) : "l"(&g_epoch) : "memory");
        const uint32_t zero = p.zero;
        const uint32_t selLo = (g & 1) ? 0x1044u : 0x4410u;
        const uint32_t selHi = (g & 1) ? 0x3244u : 0x4432u;
        const uint32_t fo0 = 2 * t * 128 + (((g >> 1) ^ (2 * t)) << 4) + (g & 1) * 8;
        const uint32_t fo1 = (2 * t + 1) * 128 + (((g >> 1) ^ (2 * t + 1)) << 4) + (g & 1) * 8;
        uint32_t W[32][4];
        uint32_t mean2;
        float inv_den;
        tag += 1;
        sts32(sb + SM_TV + 16 * tid, xw);
        ln_partial(xw, sb + SM_ST, warp, lane);
        asm volatile("bar.sync 1, 384;" ::: "memory");
        ln_final(lds128f(sb + SM_ST), lds128f(sb + SM_ST + 16), lds128f(sb + SM_ST + 32), lds128f(sb + SM_ST + 48), mean2, inv_den);

        {
            const float c0 = bf_lo(cw), c1 = bf_hi(cw);
            const uint32_t sw = pack_bf16(__fdividef(c0, 1.0f + __expf(-c0)), __fdividef(c1, 1.0f + __expf(-c1)));
            const uint32_t a = sb + SM_GU + (64 * warp + (lane & 7) + 8 * (lane >> 4)) * 48 + ((lane >> 3) & 1) * 16;
            const uint32_t a2 = sb + SM_GU + (64 * warp + lane) * 48 + 32;
            float m0[4] = {0.f, 0.f, 0.f, 0.f}, m1[4] = {0.f, 0.f, 0.f, 0.f};
            mbar_wait(bar_mod, 0);
#pragma unroll
            for (int j = 0; j < 4; j += 2) {
                uint32_t f0[4], f1[4], f2[4];
                ldsm4t(f0, a + j * 768); ldsm4t(f1, a + j * 768 + 768); ldsm4t(f2, a2 + j * 768);
                const uint32_t b0 = __shfl_sync(0xffffffffu, sw, 8 * j + t), b1 = __shfl_sync(0xffffffffu, sw, 8 * j + 4 + t);
                const uint32_t b2 = __shfl_sync(0xffffffffu, sw, 8 * j + 8 + t), b3 = __shfl_sync(0xffffffffu, sw, 8 * j + 12 + t);
                mma_f(m0, f0, b0, b1);
                mma16816(m1, f2[0], 0u, f2[1], 0u, b0, b1);
                mma_f(m0, f1, b2, b3);
                mma16816(m1, f2[2], 0u, f2[3], 0u, b2, b3);
            }
            if (t == 0) sts128f(sb + SM_R3 + (warp * 8 + g) * 16, m0[0], m0[2], m1[0], 0.f);
            cbar();
            if (warp == 0) {
                float s = 0.f;
#pragma unroll
                for (int w = 0; w < 8; w++) s += ldsf(sb + SM_R3 + w * 128 + lane * 4);
                const float s2 = __shfl_down_sync(0xffffffffu, s, 4);
                if (t < 3 && !(g & 1))
                    st_relaxed64(mod_ptr(12 * cta + 4 * t + (g >> 1)), ((unsigned long long)tag << 32) | pack_bf16(s, s2));
            }
        }
        {
            mbar_wait(bar_full + 8 * (warp & 4), 0);
            const uint32_t a = sb + SM_RING + (warp >> 2) * 65536 + (warp & 3) * 8192;
            uint32_t dep = 0;
#pragma unroll
            for (int s = 0; s < 16; s++) {
                const uint32_t as = a + (s >> 3) * 32768 + (s & 7) * 1024;
                load_frag_pair(W[2 * s], W[2 * s + 1], as + fo0, as + fo1);
                dep |= W[2 * s][0] | W[2 * s][2] | W[2 * s + 1][0] | W[2 * s + 1][2];
            }
            dep = __reduce_or_sync(0xffffffffu, dep & zero);
            if (lane < 2) mbar_arrive(bar_empty + 8 * ((warp & 4) + 2 * lane + ((warp >> 1) & 1)) + dep, 4);
        }
        {
            unsigned long long va, vc; int it = 0;
            while (true) {
                va = ld_relaxed64(mod_ptr(tid)); vc = ld_relaxed64(mod_ptr(256 + tid));
                if (__all_sync(0xffffffffu, has_tag(va, tag) && has_tag(vc, tag)) || ++it >= SPIN_LIMIT) break;
                __nanosleep(MOD_SLEEP);
            }
            const uint32_t hw = ln_mod(xw, mean2, inv_den, add2(ONE2, (uint32_t)vc), (uint32_t)va);
            float qa[4][4];
#pragma unroll
            for (int i = 0; i < 4; i++) { qa[i][0] = qa[i][1] = qa[i][2] = qa[i][3] = 0.f; }
#pragma unroll
            for (int s = 0; s < 8; s++) {
                const uint32_t w0 = __shfl_sync(0xffffffffu, hw, 4 * s + t);
                const uint32_t b0 = __byte_perm(w0, 0u, selLo), b1 = __byte_perm(w0, 0u, selHi);
                mma_f(qa[0], W[2 * s], b0, b1);
                mma_f(qa[1], W[2 * s + 1], b0, b1);
                mma_f(qa[2], W[2 * s + 16], b0, b1);
                mma_f(qa[3], W[2 * s + 17], b0, b1);
            }
            if (t == 0) {
#pragma unroll
                for (int i = 0; i < 4; i++) sts128f(sb + SM_RED + warp * 512 + i * 128 + g * 16, qa[i][0], qa[i][1], qa[i][2], qa[i][3]);
            }
            cbar();
            if (tid < 128) {
                float s = 0.f;
#pragma unroll
                for (int w = 0; w < 8; w++) s += ldsf(sb + SM_RED + w * 512 + tid * 4);
                sts16(sb + SM_VEC + 2 * tid, pack_bf16(s, 0.f));
            }
            cbar();
        }
        if (tid == 0) mbar_arrive(bar_trig + 8, 1);
        uint32_t pw[8];
#pragma unroll
        for (int i = 0; i < 8; i++) pw[i] = 0u;
        {
            uint32_t qf[16];
#pragma unroll
            for (int j = 0; j < 16; j++) qf[j] = lds32(sb + SM_VEC + ((j ^ g) << 4) + 4 * t);
            const uint32_t lrow = (lane & 7) + 8 * ((lane >> 3) & 1);
            const uint32_t loff = (warp & 3) * 4096 + lrow * 256 + (((lane >> 4) ^ (lane & 7)) << 4);
            int slot = (U_K + (warp >> 2)) % SLOTS, ph = ((U_K + (warp >> 2)) / SLOTS) & 1;
#pragma unroll 1
            for (int n = 0; n < 8; n++) {
                mbar_wait(bar_full + 8 * slot, ph);
                const uint32_t a = sb + SM_RING + slot * UNIT_BYTES + loff;
                float c0[4] = {0.f, 0.f, 0.f, 0.f}, c1[4] = {0.f, 0.f, 0.f, 0.f};
#pragma unroll
                for (int j = 0; j < 8; j += 2) {
                    uint32_t f0[4], f1[4];
                    ldsm4(f0, a ^ (32 * j));
                    ldsm4(f1, a ^ (32 * j + 32));
                    mma_f(c0, f0, qf[2 * j], qf[2 * j + 1]);
                    mma_f(c1, f1, qf[2 * j + 2], qf[2 * j + 3]);
                }
                const float slo = (g & 1) ? c0[1] + c1[1] : c0[0] + c1[0];
                const float shi = (g & 1) ? c0[3] + c1[3] : c0[2] + c1[2];
                uint32_t r = pack_bf16(slo, shi);
                if (lane == 0) mbar_arrive(bar_empty + 8 * slot + (r & zero), 2);
                r = pack_bf16(bf_lo(r) * 0.08838834764831845f, bf_hi(r) * 0.08838834764831845f);
#pragma unroll
                for (int i = 0; i < 7; i++) pw[i] = pw[i + 1];
                pw[7] = r;
                slot += n < 4 ? 2 : 4; if (slot >= SLOTS) { slot -= SLOTS; ph ^= 1; }
                if (n == 4 + (warp >> 1)) {
                    const int u = U_WO + 4 * (warp >> 1) + (warp & 1), ws = u % SLOTS;
                    mbar_wait(bar_full + 8 * ws, (u / SLOTS) & 1);
                    const uint32_t wa = sb + SM_RING + ws * UNIT_BYTES;
                    uint32_t dep = 0;
#pragma unroll
                    for (int s = 0; s < 16; s++) {
                        const uint32_t as = wa + ((s * 1024 + (cta & 3) * 4096) & 16383);
                        load_frag_pair(W[2 * s], W[2 * s + 1], as + fo0, as + fo1);
                        dep |= W[2 * s][0] | W[2 * s][2] | W[2 * s + 1][0] | W[2 * s + 1][2];
                    }
                    dep = __reduce_or_sync(0xffffffffu, dep & zero);
                    if (lane == 0) mbar_arrive(bar_empty + 8 * ws + dep, 8);
                }
            }
        }
        if (tid == 0) mbar_arrive(bar_trig, 1);
        float mw;
        {
            const bool valid = (t == (g >> 1));
            if (valid) st_relaxed64(&g_ls[(cta * 8 + warp) * 8 + g], ((unsigned long long)tag << 32) | pw[7]);
            mw = -INFINITY;
#pragma unroll
            for (int i = 0; i < 8; i++) mw = fmaxf(mw, fmaxf(bf_lo(pw[i]), bf_hi(pw[i])));
            if (!valid) mw = -INFINITY;
#pragma unroll
            for (int o = 16; o > 0; o >>= 1) mw = fmaxf(mw, __shfl_xor_sync(0xffffffffu, mw, o));
            float lw = 0.f;
#pragma unroll
            for (int i = 0; i < 8; i++) {
                const float e0 = valid ? __expf(bf_lo(pw[i]) - mw) : 0.f, e1 = valid ? __expf(bf_hi(pw[i]) - mw) : 0.f;
                lw += e0 + e1;
                pw[i] = pack_bf16(e0, e1);
            }
#pragma unroll
            for (int o = 16; o > 0; o >>= 1) lw += __shfl_xor_sync(0xffffffffu, lw, o);
            if (lane < 2)
                st_relaxed64(&g_stat[(cta * 8 + warp) * 2 + lane], ((unsigned long long)tag << 32) | __float_as_uint(lane ? lw : mw));
        }
        float acc[8][4];
#pragma unroll
        for (int i = 0; i < 8; i++) { acc[i][0] = acc[i][1] = acc[i][2] = acc[i][3] = 0.f; }
        float scale = 0.f;
        const int pl = 16 * (t >> 1) + 2 * g + (t & 1);
        float4* redp = &g_acc[acc_idx(32 * warp + pl)];
        asm volatile("" : "+l"(redp));
        float4* const pollp = redp;
        float4 v;
        {
            const uint32_t lrow = (lane & 7) + 8 * (lane >> 4);
            const uint32_t loff = (warp & 3) * 4096 + lrow * 256 + ((((lane >> 3) & 1) ^ (lane & 7)) << 4);
            int slot = (U_V + (warp >> 2)) % SLOTS, ph = ((U_V + (warp >> 2)) / SLOTS) & 1;
#pragma unroll 1
            for (int n = 0; n < 7; n++) {
                if (n == 2 && tid == 0) mbar_arrive(bar_trig + 16, 1);
                if (n == 6) {
                    mbar_wait(bar_aux, 0);
                    scale = __expf(mw - ldsf(sb + SM_ML)) * ldsf(sb + SM_ML + 4);
                }
                const uint32_t b0 = __byte_perm(pw[0], 0u, selLo), b1 = __byte_perm(pw[0], 0u, selHi);
#pragma unroll
                for (int i = 0; i < 6; i++) pw[i] = pw[i + 1];
                mbar_wait(bar_full + 8 * slot, ph);
                const uint32_t a = sb + SM_RING + slot * UNIT_BYTES + loff;
                uint32_t dep = 0;
#pragma unroll
                for (int c = 0; c < 8; c++) {
                    uint32_t f[4];
                    ldsm4t(f, a ^ (32 * c));
                    mma_f(acc[c], f, b0, b1);
                    dep |= f[0];
                }
                if (lane == 0) mbar_arrive(bar_empty + 8 * slot + (dep & zero), 2);
                slot += 2; if (slot >= SLOTS) { slot -= SLOTS; ph ^= 1; }
            }
        }
        {
            float e[8], f[8];
#pragma unroll
            for (int c = 0; c < 8; c++) { e[c] = acc[c][0] + acc[c][3]; f[c] = acc[c][1] + acc[c][2]; }
            float e2[4], f2[4];
#pragma unroll
            for (int c = 0; c < 8; c += 2) {
                e2[c >> 1] = e[c] + __shfl_xor_sync(0xffffffffu, e[c + 1], 1);
                f2[c >> 1] = f[c] + __shfl_xor_sync(0xffffffffu, f[c + 1], 1);
            }
            const float o0 = e2[0] + __shfl_xor_sync(0xffffffffu, e2[1], 2);
            const float o1 = f2[0] + __shfl_xor_sync(0xffffffffu, f2[1], 2);
            const float o2 = e2[2] + __shfl_xor_sync(0xffffffffu, e2[3], 2);
            const float o3 = f2[2] + __shfl_xor_sync(0xffffffffu, f2[3], 2);
            sts128f(sb + SM_RED + tid * 16, o0 * scale, o1 * scale, o2 * scale, o3 * scale);
            cbar();
            if (tid < 128) {
                const uint32_t rp = sb + SM_RED + tid * 4;
                const float s = ((ldsf(rp) + ldsf(rp + 512)) + (ldsf(rp + 1024) + ldsf(rp + 1536))) +
                                ((ldsf(rp + 2048) + ldsf(rp + 2560)) + (ldsf(rp + 3072) + ldsf(rp + 3584)));
                const int comp = tid & 3, tt = (tid >> 2) & 3, gg = tid >> 4;
                const int sidx = (8 * (comp >> 1) + 2 * tt + (comp & 1) - 4 * (cta & 3)) & 15;
                sts16(sb + SM_VEC + 2 * ((gg >> 1) * 32 + 2 * sidx + (gg & 1)), pack_bf16(s, 0.f));
            }
            cbar();
            uint4 ov[4];
#pragma unroll
            for (int i = 0; i < 4; i++) ov[i] = lds128(sb + SM_VEC + 64 * t + 16 * i);
            const uint32_t* ow = reinterpret_cast<const uint32_t*>(ov);
#pragma unroll
            for (int i = 0; i < 8; i++) { acc[i][0] = acc[i][1] = acc[i][2] = acc[i][3] = 0.f; }
#pragma unroll
            for (int s = 0; s < 16; s++) {
                const uint32_t b0 = __byte_perm(ow[s], 0u, selLo), b1 = __byte_perm(ow[s], 0u, selHi);
                mma_f(acc[2 * (s & 3)], W[2 * s], b0, b1);
                mma_f(acc[2 * (s & 3) + 1], W[2 * s + 1], b0, b1);
            }
#pragma unroll
            for (int i = 0; i < 4; i++) {
                acc[0][i] = (acc[0][i] + acc[2][i]) + (acc[4][i] + acc[6][i]);
                acc[1][i] = (acc[1][i] + acc[3][i]) + (acc[5][i] + acc[7][i]);
                acc[2][i] = acc[3][i] = acc[4][i] = acc[5][i] = acc[6][i] = acc[7][i] = 0.f;
            }
        }
        const uint4 tv = lds128(sb + SM_TV + 16 * (32 * warp + pl));
        const uint32_t gb = lds32(sb + SM_GB + 4 * (32 * warp + pl));
        uint32_t* outp = reinterpret_cast<uint32_t*>(p.out) + 32 * warp + pl;
        asm volatile("" : "+l"(outp));
        const uint32_t bvw = sb + SM_BV + warp * 576 + ((pl & 3) * 8 + 2 * (pl >> 3) + ((pl >> 2) & 1)) * 4;
        const uint32_t bvr = sb + SM_BV + warp * 576 + (g & 3) * 144 + t * 32;
        sts32(bvw + 288, tv.z); sts32(bvw + 432, tv.w);
        uint32_t agu = sb + SM_GU + (64 * warp + (lane & 7) + 8 * (lane >> 4)) * 32 + ((((lane >> 3) ^ (lane >> 2)) & 1) << 4);
        uint32_t ad0 = sb + SM_WD + warp * 2048 + fo0, ad1 = sb + SM_WD + warp * 2048 + fo1, ad2 = ad0 ^ 64, ad3 = ad1 ^ 64;
        uint32_t ars = (t & 1) ? sb + SM_RED + 1024 + warp * 256 + (4 * g + (t & 2)) * 8 : sb + SM_RED + warp * 128 + (4 * g + t) * 4;
        asm volatile("" : "+r"(agu), "+r"(ad0), "+r"(ad1), "+r"(ad2), "+r"(ad3), "+r"(ars));
        {
            uint32_t pb[8];
#pragma unroll
            for (int i = 0; i < 8; i++) pb[i] = lds32(sb + SM_PL + (32 * warp + 4 * i + t) * 4);
            const int lu = NUNIT - 2 + (warp >> 2);
            const uint32_t la = sb + SM_RING + (lu % SLOTS) * UNIT_BYTES + (warp & 3) * 4096 + ((lane & 7) + 8 * (lane >> 4)) * 64 +
                                ((((lane >> 3) & 1) ^ ((lane & 7) >> 1)) << 4);
            mbar_wait(bar_full + 8 * (lu % SLOTS), (lu / SLOTS) & 1);
#pragma unroll
            for (int ks = 0; ks < 4; ks++) {
                uint32_t f0[4], f1[4];
                ldsm4t(f0, la + ks * 1024); ldsm4t(f1, (la + ks * 1024) ^ 32);
                mma_f(acc[4 + (ks & 1)], f0, pb[2 * ks], pb[2 * ks + 1]);
                mma_f(acc[6 + (ks & 1)], f1, pb[2 * ks], pb[2 * ks + 1]);
            }
            if (t == 0) sts128f(sb + SM_R3 + (warp * 8 + g) * 16, acc[4][0] + acc[5][0], acc[4][2] + acc[5][2], acc[6][0] + acc[7][0], acc[6][2] + acc[7][2]);
            cbar();
            const uint32_t rp = sb + SM_R3 + 4 * lane;
            const uint32_t ol = pack_bf16(((ldsf(rp) + ldsf(rp + 128)) + (ldsf(rp + 256) + ldsf(rp + 384))) +
                                          ((ldsf(rp + 512) + ldsf(rp + 640)) + (ldsf(rp + 768) + ldsf(rp + 896))), 0.f);
#pragma unroll
            for (int s = 0; s < 4; s++) {
                const uint32_t b0 = __byte_perm(__shfl_sync(0xffffffffu, ol, 8 * t + s), 0u, selLo);
                const uint32_t b1 = __byte_perm(__shfl_sync(0xffffffffu, ol, 8 * t + 4 + s), 0u, selLo);
                mma_f(acc[2 * (s & 1)], W[2 * s], b0, b1);
                mma_f(acc[2 * (s & 1) + 1], W[2 * s + 1], b0, b1);
            }
            float X[4];
#pragma unroll
            for (int i = 0; i < 4; i++) X[i] = (t & 2) ? acc[1][i] + acc[3][i] : acc[0][i] + acc[2][i];
            const float a0 = (t & 1) ? X[2] : X[0], a1 = (t & 1) ? X[3] : X[1];
            if (is_ffn) {
                v = atom_f4(redp, a0, a1, 1.0f, 0.0f);
                v.x += a0; v.y += a1; v.z += 1.0f;
            } else {
                red_f4(redp, a0, a1, 1.0f, 0.0f);
                v = make_float4(0.f, 0.f, 0.f, 0.f);
            }
        }
        if (is_ffn) {
            uint32_t fg[4][4], fu[4][4], fd[4][4];
            bool have_gu = false;
#define LOAD_GU() do { \
                _Pragma("unroll") for (int j = 0; j < 4; j++) { ldsm4t(fg[j], agu + j * 512); ldsm4t(fu[j], agu + 16384 + j * 512); } \
                have_gu = true; } while (0)
#define LOAD_WD() do { lds64(fd[0][0], fd[0][1], ad0); lds64(fd[0][2], fd[0][3], ad1); lds64(fd[1][0], fd[1][1], ad2); lds64(fd[1][2], fd[1][3], ad3); \
                lds64(fd[2][0], fd[2][1], ad0 + 1024); lds64(fd[2][2], fd[2][3], ad1 + 1024); lds64(fd[3][0], fd[3][1], ad2 + 1024); lds64(fd[3][2], fd[3][3], ad3 + 1024); } while (0)
#define TRY_GU() do { if (!have_gu && mbar_test(bar_gu, 0)) LOAD_GU(); } while (0)
            int it = 0;
            while (true) {
                if (it > 0) {
                    const uint32_t c0 = clock32(), w = min((uint32_t)((float)NCTA - __shfl_sync(0xffffffffu, v.z, 0)), (uint32_t)NCTA) * POLL_K;
                    while (clock32() - c0 < w) { }
                    v = ld_relaxed_f4(pollp);
                }
                TRY_GU();
                if (__all_sync(0xffffffffu, v.z == (float)NCTA) || ++it >= SPIN_LIMIT) break;
            }
            const uint32_t yw = residual(tv.x, tv.y, v.x, v.y);
            if (!have_gu) { mbar_wait(bar_gu, 0); LOAD_GU(); }
            float s;
            {
                const float ya = bf_lo(yw), yb = bf_hi(yw);
                const uint32_t zh = mul2(yw, tv.z);
                sts32(bvw, zh);
                sts32(bvw + 144, pack_bf16(fmaf(ya, bf_lo(tv.z), -bf_lo(zh)), fmaf(yb, bf_hi(tv.z), -bf_hi(zh))));
                float ls = ya + yb, lm = (ya - yb) * (ya - yb) * 0.5f, so, mo, d;
#define LN_ROUND(o) so = __shfl_xor_sync(0xffffffffu, ls, o); mo = __shfl_xor_sync(0xffffffffu, lm, o); d = ls - so; ls += so; lm = fmaf(d * d, 0.25f / o, lm + mo)
                __syncwarp();
                LN_ROUND(1);
                const uint4 bA = lds128(bvr), bB = lds128(bvr + 16);
                LN_ROUND(2);
                float cg[2][4], cu[2][4];
#pragma unroll
                for (int i = 0; i < 4; i++) { cg[0][i] = cg[1][i] = cu[0][i] = cu[1][i] = 0.f; }
                mma_f(cg[0], fg[0], bA.x, bA.y); mma_f(cu[0], fu[0], bA.x, bA.y);
                mma_f(cg[1], fg[1], bA.z, bA.w); mma_f(cu[1], fu[1], bA.z, bA.w);
                LN_ROUND(4);
                mma_f(cg[0], fg[2], bB.x, bB.y); mma_f(cu[0], fu[2], bB.x, bB.y);
                mma_f(cg[1], fg[3], bB.z, bB.w); mma_f(cu[1], fu[3], bB.z, bB.w);
                LN_ROUND(8);
                LN_ROUND(16);
                float r[4];
#pragma unroll
                for (int i = 0; i < 4; i++) r[i] = (t & 2) ? cu[0][i] + cu[1][i] : cg[0][i] + cg[1][i];
                if (t & 1) sts128f(ars, r[0], r[1], r[2], r[3]);
                else sts64f(ars, r[0] + r[1], r[2] + r[3]);
                if (lane == 0) sts64f(sb + SM_ST + 64 + 8 * warp, ls, lm);
                mbar_wait(bar_wd, 0);
                LOAD_WD();
                cbar();
                const float4 q0 = lds128f(sb + SM_ST + 64), q1 = lds128f(sb + SM_ST + 80), q2 = lds128f(sb + SM_ST + 96), q3 = lds128f(sb + SM_ST + 112);
                const uint32_t rp = sb + SM_RED + 4 * lane;
                const float r0 = ldsf(rp), r1 = ldsf(rp + 128), r2 = ldsf(rp + 256), r3 = ldsf(rp + 384);
                const float r4 = ldsf(rp + 512), r5 = ldsf(rp + 640), r6 = ldsf(rp + 768), r7 = ldsf(rp + 896);
                uint32_t bb[8], cc[8];
#pragma unroll
                for (int w = 0; w < 8; w++) lds64(bb[w], cc[w], sb + SM_RED + 1024 + w * 256 + 8 * lane);
#define F_(x) __uint_as_float(x)
                const float vb = ((F_(bb[0]) + F_(bb[1])) + (F_(bb[2]) + F_(bb[3]))) + ((F_(bb[4]) + F_(bb[5])) + (F_(bb[6]) + F_(bb[7])));
                const float vc = ((F_(cc[0]) + F_(cc[1])) + (F_(cc[2]) + F_(cc[3]))) + ((F_(cc[4]) + F_(cc[5])) + (F_(cc[6]) + F_(cc[7])));
                ln_final(q0, q1, q2, q3, mean2, inv_den);
                s = rbf(fmaf(fmaf(-bf_lo(mean2), vb, ((r0 + r1) + (r2 + r3)) + ((r4 + r5) + (r6 + r7))), inv_den, vc));
            }
            const uint32_t hh = pack_bf16(s * __shfl_xor_sync(0xffffffffu, s, 2), 0.f);
            uint32_t b[4];
#pragma unroll
            for (int i = 0; i < 4; i++) b[i] = __byte_perm(__shfl_sync(0xffffffffu, hh, 8 * t + 4 * (i & 1) + (i >> 1)), 0u, selLo);
            float X[4] = {0.f, 0.f, 0.f, 0.f}, Y[4] = {0.f, 0.f, 0.f, 0.f}, X2[4] = {0.f, 0.f, 0.f, 0.f}, Y2[4] = {0.f, 0.f, 0.f, 0.f};
            mma_f(X, fd[0], b[0], b[1]);
            mma_f(Y, fd[1], b[0], b[1]);
            mma_f(X2, fd[2], b[2], b[3]);
            mma_f(Y2, fd[3], b[2], b[3]);
#pragma unroll
            for (int i = 0; i < 4; i++) { const float xa = X[i] + X2[i], ya = Y[i] + Y2[i]; X[i] = (t & 2) ? ya : xa; }
            const float v0 = (t & 1) ? X[2] : X[0], v1 = (t & 1) ? X[3] : X[1];
            const float4 old = atom_f4(redp + ACC2_OFF, v0, v1, 1.0f, 0.0f);
            if (old.z == (float)(NFFN - 1)) *outp = residual(yw, gb, old.x + v0, old.y + v1);
            if (cta == 0 && tid == 0) g_epoch = tag;
        }
    } else {
        asm volatile("setmaxnreg.dec.sync.aligned.u32 40;");
        if (tid == 256) {
            mbar_init(bar_mod, 1);
            mbar_init(bar_full, 1);
            mbar_init(bar_full + 8 * 4, 1);
            asm volatile("fence.mbarrier_init.release.cluster;" ::: "memory");
            mbar_expect_tx(bar_mod, 24576);
            tma2d(sb + SM_GU, &p.m_mod, 24 * cta, 0, bar_mod);
            tma2d(sb + SM_GU + 12288, &p.m_mod, 24 * cta, 256, bar_mod);
            mbar_expect_tx(bar_full, 65536);
            tma3d(sb + SM_RING, &p.m_wq, 0, 0, 2 * head, bar_full);
            mbar_expect_tx(bar_full + 8 * 4, 65536);
            tma3d(sb + SM_RING + 65536, &p.m_wq, 0, 256, 2 * head, bar_full + 8 * 4);
        } else if (tid == 288) {
            mbar_init(bar_full + 8 * U_K, 1);
            asm volatile("fence.mbarrier_init.release.cluster;" ::: "memory");
            mbar_expect_tx(bar_full + 8 * U_K, UNIT_BYTES);
            bulk_g2s(sb + SM_RING + U_K * UNIT_BYTES, (const char*)p.k + (size_t)cta * (16 * UNIT_BYTES), UNIT_BYTES, bar_full + 8 * U_K);
            bulk_pf((const char*)p.k + (size_t)cta * (16 * UNIT_BYTES) + UNIT_BYTES, UNIT_BYTES);
#pragma unroll
            for (int s = 0; s < SLOTS; s++) {
                if (s != 0 && s != 4 && s != U_K) mbar_init(bar_full + 8 * s, 1);
                mbar_init(bar_empty + 8 * s, 8);
            }
            mbar_init(bar_gu, 2); mbar_init(bar_aux, 2); mbar_init(bar_wd, 1); mbar_init(bar_go, 1);
            mbar_init(bar_trig, 1); mbar_init(bar_trig + 8, 1); mbar_init(bar_trig + 16, 1);
            asm volatile("fence.mbarrier_init.release.cluster;" ::: "memory");
#pragma unroll
            for (int s = 1; s < U_K; s++) if (s != 4) mbar_arrive(bar_full + 8 * s, 1);
        }
        const uint32_t t_start = gtime32();
        __syncwarp();
        asm volatile("bar.sync 1, 384;" ::: "memory");
        if (warp == 8) {
            if (lane == 0) {
                const char* kb = (const char*)p.k + (size_t)cta * (16 * UNIT_BYTES);
                const char* vb = (const char*)p.v + (size_t)cta * (16 * UNIT_BYTES) - 18 * UNIT_BYTES;
                const char* ob = (const char*)p.wo + (size_t)cta * (2 * UNIT_BYTES) - 4 * UNIT_BYTES;
                constexpr int U0 = U_K + 1;
                uint32_t slot = U0 % SLOTS, ph = ((U0 / SLOTS) & 1) ^ 1;
                uint32_t sa = (U0 - WMAX) % SLOTS, pa = ((U0 - WMAX) / SLOTS) & 1;
                uint32_t sn = (U0 - WMIN) % SLOTS, pn = ((U0 - WMIN) / SLOTS) & 1;
                const uint32_t t_base = t_start + T_A;
                uint32_t now = t_start;
                int pj = 2;
                int j = 1, wo = 0;
#pragma unroll 1
                for (int u = U0; u < NUNIT; u++) {
                    const bool is_wo = (u >= U_WO && u < U_V && !((u - U_WO) & 2));
#pragma unroll 1
                    for (int it = 0; it < SPIN_LIMIT; it++) {
                        const bool calm = u - WMAX < U_K || mbar_test(bar_full + 8 * sa, pa);
                        const bool ok = calm && (u < SLOTS || mbar_test(bar_empty + 8 * slot, ph));
                        if (ok && (is_wo || pj > j)) break;
                        if ((int)(now - (t_base + pj * TAU)) >= 0 || (ok && u - WMIN >= U_K && mbar_test(bar_full + 8 * sn, pn))) {
                            if (ok && pj == j) { pj++; break; }
                            if (calm && pj < j + PFMAX && pj < 34) {
                                bulk_pf((pj < 4 ? kb : (pj < 6 ? ob : (pj < 18 ? kb - 2 * UNIT_BYTES : vb))) + (size_t)pj * UNIT_BYTES, UNIT_BYTES);
                                pj++;
                                continue;
                            }
                        }
                        now = gtime32();
                    }
                    const uint32_t dst = sb + SM_RING + slot * UNIT_BYTES, bar = bar_full + 8 * slot;
                    mbar_expect_tx(bar, UNIT_BYTES);
                    if (is_wo) { tma3d(dst, &p.m_wo, 0, head * 128, wo, bar); wo++; }
                    else if (u >= NUNIT - 2) {
                        const int row = head * 4096 + (u - (NUNIT - 2)) * 2048 + 896;
                        tma2d(dst, &p.m_v, 32 * (cta & 3), row, bar);
                        tma2d(dst + 8192, &p.m_v, 32 * (cta & 3), row + 1024, bar);
                        j++;
                    } else {
                        bulk_g2s(dst, (j < 4 ? kb : (j < 18 ? kb - 2 * UNIT_BYTES : vb)) + (size_t)j * UNIT_BYTES, UNIT_BYTES, bar);
                        j += (j == 3) ? 3 : 1;
                    }
                    if (++slot == SLOTS) { slot = 0; ph ^= 1; }
                    if (++sa == SLOTS) { sa = 0; pa ^= 1; }
                    if (++sn == SLOTS) { sn = 0; pn ^= 1; }
                }
                if (is_ffn) {
                    mbar_expect_tx(bar_wd, 16384);
#pragma unroll 1
                    for (int it = 0; it < SPIN_LIMIT; it++)
                        if ((int)(gtime32() - (t_start + (uint32_t)(T_A + 34 * TAU + GU_DELAY))) >= 0 ||
                            mbar_test(bar_full + 8 * (GU_FORCE % SLOTS), (GU_FORCE / SLOTS) & 1)) break;
                    mbar_wait(bar_full + 8 * (GU_UNIT % SLOTS), (GU_UNIT / SLOTS) & 1);
                    mbar_arrive(bar_go, 1);
                    uint32_t due = clock32() + WD_LAG;
#pragma unroll 1
                    for (int i = 0; i < 8; i++) {
#pragma unroll 1
                        for (int it = 0; it < SPIN_LIMIT; it++) if ((int)(clock32() - due) >= 0) break;
                        due += WD_PACE;
                        tma3d(sb + SM_WD + i * 2048, &p.m_wd, 0, 16 * ffn, i, bar_wd);
                    }
                }
            }
        } else {
            uint32_t tag;
            asm volatile("ld.relaxed.gpu.global.u32 %0, [%1];" : "=r"(tag) : "l"(&g_epoch) : "memory");
            tag += 1;
            if (warp == 9) {
                if (lane == 0) {
                    asm volatile("prefetch.tensormap [%0];" :: "l"(&p.m_wo) : "memory");
                    asm volatile("prefetch.tensormap [%0];" :: "l"(&p.m_wg) : "memory");
                    asm volatile("prefetch.tensormap [%0];" :: "l"(&p.m_wu) : "memory");
                    asm volatile("prefetch.tensormap [%0];" :: "l"(&p.m_wd) : "memory");
                    asm volatile("prefetch.tensormap [%0];" :: "l"(&p.m_v) : "memory");
                }
                if (cta == ZERO_CTA) {
                    mbar_wait(bar_trig, 0);
#pragma unroll 1
                    for (int i = 0; i < 16; i++) g_acc[acc_idx(32 * i + lane)] = make_float4(0.f, 0.f, 0.f, 0.f);
                    asm volatile("fence.acq_rel.gpu;" ::: "memory");
                    __syncwarp();
                    if (lane < 4) st_relaxed64(&g_zflag[lane], (unsigned long long)tag << 32);
                }
            } else if (warp == 10) {
                if (is_ffn) {
                    mbar_wait(bar_trig + 8, 0);
#pragma unroll 1
                    for (int i = 2 * lane; i < 256; i += 64) {
                        unsigned long long q[8]; int it = 0; bool ok;
                        do {
                            ok = true;
#pragma unroll
                            for (int k = 0; k < 4; k++) {
                                asm volatile("ld.relaxed.gpu.global.v2.u64 {%0,%1}, [%2];" : "=l"(q[2 * k]), "=l"(q[2 * k + 1]) : "l"(mod_ptr(512 + 256 * k + i)) : "memory");
                                ok = ok && has_tag(q[2 * k], tag) && has_tag(q[2 * k + 1], tag);
                            }
                        } while (!ok && ++it < SPIN_LIMIT);
#pragma unroll
                        for (int e = 0; e < 2; e++) {
                            sts32(sb + SM_TV + 16 * (i + e) + 4, (uint32_t)q[e]);
                            sts32(sb + SM_TV + 16 * (i + e) + 8, add2(ONE2, (uint32_t)q[4 + e]));
                            sts32(sb + SM_TV + 16 * (i + e) + 12, (uint32_t)q[2 + e]);
                            sts32(sb + SM_GB + 4 * (i + e), (uint32_t)q[6 + e]);
                        }
                    }
                }
                __syncwarp();
                if (lane == 0) mbar_arrive(bar_aux, 1);
            } else {
                mbar_wait(bar_trig + 16, 0);
                const unsigned long long* sp = &g_stat[(head * 32 + lane) * 2];
                const unsigned long long* lp = &g_ls[head * 256 + lane];
                unsigned long long q0, q1, q2; uint32_t w[8]; int it = 0;
                while (true) {
                    bool ok = true;
                    q0 = ld_relaxed64(sp); q1 = ld_relaxed64(sp + 1);
#pragma unroll
                    for (int i = 0; i < 8; i++) { const unsigned long long v = ld_relaxed64(lp + 32 * i); w[i] = (uint32_t)v; ok = ok && has_tag(v, tag); }
                    asm volatile("ld.acquire.gpu.global.u64 %0, [%1];" : "=l"(q2) : "l"(g_zflag) : "memory");
                    if (__all_sync(0xffffffffu, ok && has_tag(q0, tag) && has_tag(q1, tag) && has_tag(q2, tag)) || ++it >= SPIN_LIMIT) break;
                    __nanosleep(500);
                }
                const float mi = __uint_as_float((uint32_t)q0);
                float m = mi;
#pragma unroll
                for (int o = 16; o > 0; o >>= 1) m = fmaxf(m, __shfl_xor_sync(0xffffffffu, m, o));
                float l = __uint_as_float((uint32_t)q1) * __expf(mi - m);
#pragma unroll
                for (int o = 16; o > 0; o >>= 1) l += __shfl_xor_sync(0xffffffffu, l, o);
                const float il = __fdividef(1.0f, l);
#pragma unroll
                for (int i = 0; i < 8; i++) {
                    const uint32_t pp = pack_bf16(__expf(bf_lo(w[i]) - m) * il, __expf(bf_hi(w[i]) - m) * il);
                    const uint32_t a = sb + SM_PL + (16 * (i * 4 + (lane >> 3)) + (lane & 7)) * 2;
                    sts16(a, pp); sts16(a + 16, pp >> 16);
                }
                __syncwarp();
                if (lane == 0) {
                    sts64f(sb + SM_ML, m, il);
                    mbar_arrive(bar_aux, 1);
                }
            }
            if (warp < 11 && is_ffn && lane == 0) {
                const CUtensorMap* m = warp == 9 ? &p.m_wg : &p.m_wu;
                const uint32_t dst = sb + SM_GU + (warp - 9) * 16384;
                mbar_expect_tx(bar_gu, 16384);
                mbar_wait(bar_go, 0);
                uint32_t due = clock32() + (warp - 9) * (GU_PACE / 2);
#pragma unroll 1
                for (int i = 0; i < 512 / GU_ROWS; i++) {
#pragma unroll 1
                    for (int it = 0; it < SPIN_LIMIT; it++) if ((int)(clock32() - due) >= 0) break;
                    due += GU_PACE;
                    tma2d(dst + i * (GU_ROWS * 32), m, 16 * ffn, GU_ROWS * i, bar_gu);
                }
            }
        }
    }
}

typedef CUresult (*EncodeFn)(CUtensorMap*, CUtensorMapDataType, cuuint32_t, void*, const cuuint64_t*, const cuuint64_t*,
                             const cuuint32_t*, const cuuint32_t*, CUtensorMapInterleave, CUtensorMapSwizzle,
                             CUtensorMapL2promotion, CUtensorMapFloatOOBfill);
static void encode2d(EncodeFn f, CUtensorMap* m, const void* ptr, int cols, int rows, int bc, int br, CUtensorMapSwizzle sw, CUtensorMapL2promotion pr) {
    cuuint64_t dim[2] = {(cuuint64_t)cols, (cuuint64_t)rows};
    cuuint64_t str[1] = {(cuuint64_t)cols * 2};
    cuuint32_t box[2] = {(cuuint32_t)bc, (cuuint32_t)br};
    cuuint32_t es[2] = {1, 1};
    f(m, CU_TENSOR_MAP_DATA_TYPE_BFLOAT16, 2, (void*)ptr, dim, str, box, es, CU_TENSOR_MAP_INTERLEAVE_NONE, sw,
      pr, CU_TENSOR_MAP_FLOAT_OOB_FILL_NONE);
}
static void encode3d(EncodeFn f, CUtensorMap* m, const void* ptr, int cols, int rows, int br, int bb) {
    cuuint64_t dim[3] = {64, (cuuint64_t)rows, (cuuint64_t)(cols / 64)};
    cuuint64_t str[2] = {(cuuint64_t)cols * 2, 128};
    cuuint32_t box[3] = {64, (cuuint32_t)br, (cuuint32_t)bb};
    cuuint32_t es[3] = {1, 1, 1};
    f(m, CU_TENSOR_MAP_DATA_TYPE_BFLOAT16, 3, (void*)ptr, dim, str, box, es, CU_TENSOR_MAP_INTERLEAVE_NONE, CU_TENSOR_MAP_SWIZZLE_128B,
      CU_TENSOR_MAP_L2_PROMOTION_L2_128B, CU_TENSOR_MAP_FLOAT_OOB_FILL_NONE);
}

extern "C" void kernel_launch(void* const* d_in, const int* in_sizes, int n_in, void* d_out, int out_size) {
    Params p;
    void* fn = nullptr;
    cudaDriverEntryPointQueryResult qr;
    cudaGetDriverEntryPoint("cuTensorMapEncodeTiled", &fn, cudaEnableDefault, &qr);
    EncodeFn enc = (EncodeFn)fn;
    encode2d(enc, &p.m_mod, d_in[10], 3072, 512, 24, 256, CU_TENSOR_MAP_SWIZZLE_NONE, CU_TENSOR_MAP_L2_PROMOTION_L2_128B);
    encode3d(enc, &p.m_wq, d_in[3], 4096, 512, 256, 2);
    encode3d(enc, &p.m_wo, d_in[4], 512, 4096, 128, 1);
    encode3d(enc, &p.m_wd, d_in[8], 512, 1376, 16, 1);
    encode2d(enc, &p.m_v, d_in[2], 128, 32 * 4096, 32, 128, CU_TENSOR_MAP_SWIZZLE_64B, CU_TENSOR_MAP_L2_PROMOTION_L2_256B);
    encode2d(enc, &p.m_wg, d_in[6], 1376, 512, 16, GU_ROWS, CU_TENSOR_MAP_SWIZZLE_32B, CU_TENSOR_MAP_L2_PROMOTION_L2_128B);
    encode2d(enc, &p.m_wu, d_in[7], 1376, 512, 16, GU_ROWS, CU_TENSOR_MAP_SWIZZLE_32B, CU_TENSOR_MAP_L2_PROMOTION_L2_128B);
    p.x = (const __nv_bfloat16*)d_in[0];
    p.k = (const __nv_bfloat16*)d_in[1];
    p.v = (const __nv_bfloat16*)d_in[2];
    p.wo = (const __nv_bfloat16*)d_in[4];
    p.c = (const __nv_bfloat16*)d_in[9];
    p.out = (__nv_bfloat16*)d_out;
    p.zero = 0;
    cudaFuncSetAttribute(fused_decode_kernel, cudaFuncAttributeMaxDynamicSharedMemorySize, SM_TOTAL);
    fused_decode_kernel<<<NCTA, NTHREADS, SM_TOTAL>>>(p);
}
```

```cpp
#include <cuda_runtime.h>
#include <cuda.h>
#include <cuda_bf16.h>
#include <stdint.h>

#define NCTA 128
#define NTHREADS 384
#define UNIT_BYTES 16384
#define SLOTS 10
#define U_K 8
#define U_WO 18
#define U_V 32
#define NUNIT 48
#define NFFN 86
#define ZERO_CTA 125
#define SPIN_LIMIT (1 << 18)
#define MBAR_LIMIT (1 << 14)
#define TAU 655
#define T_A 1100
#define PFMAX 5
#define GU_DELAY 250
#define GU_UNIT 44
#define GU_FORCE 46
#define GU_PACE 220
#define WD_LAG 1760
#define WD_PACE 120
#define WMIN 2
#define WMAX 6
#define GU_ROWS 64
#define POLL_K 5
#define MOD_SLEEP 200
static_assert(WMAX <= SLOTS - 4, "a consumer may only wait on a slot whose previous use has landed");

#define SM_RING 0
#define SM_GU (SLOTS * UNIT_BYTES)
#define SM_WD (SM_GU + 32768)
#define SM_RED (SM_WD + 16384)
#define SM_VEC (SM_RED + 4096)
#define SM_ST (SM_VEC + 256)
#define SM_ML (SM_ST + 128)
#define SM_R3 (SM_ML + 16)
#define SM_TV (SM_R3 + 1024)
#define SM_GB (SM_TV + 4096)
#define SM_PL (SM_GB + 1024)
#define SM_BV (SM_PL + 1024)
#define SM_BAR (SM_BV + 4608)
#define SM_TOTAL (SM_BAR + 8 * (2 * SLOTS + 8))

struct Params {
    const __nv_bfloat16 *k, *v, *x, *c, *wo;
    __nv_bfloat16* out;
    uint32_t zero;
    CUtensorMap m_mod, m_wq, m_wo, m_wg, m_wu, m_wd, m_v;
};

__device__ unsigned int g_epoch;
__device__ __align__(1024) unsigned long long g_zflag[4];
__device__ __align__(1024) unsigned long long g_mod[96 * 128];
__device__ __align__(1024) unsigned long long g_stat[32 * 32 * 2];
__device__ __align__(1024) unsigned long long g_ls[NCTA * 64];
#define ACC2_OFF (32 * 64)
__device__ __align__(1024) float4 g_acc[2 * 32 * 64];

__device__ __forceinline__ uint32_t gtime32() { uint32_t t; asm volatile("mov.u32 %0, %globaltimer_lo;" : "=r"(t) :: "memory"); return t; }
__device__ __forceinline__ uint32_t clock32() { uint32_t t; asm volatile("mov.u32 %0, %clock;" : "=r"(t) :: "memory"); return t; }

__device__ __forceinline__ uint32_t smem_u32(const void* p) { return (uint32_t)__cvta_generic_to_shared(p); }
__device__ __forceinline__ void mbar_init(uint32_t bar, uint32_t cnt) { asm volatile("mbarrier.init.shared::cta.b64 [%0], %1;" :: "r"(bar), "r"(cnt) : "memory"); }
__device__ __forceinline__ void mbar_expect_tx(uint32_t bar, uint32_t bytes) { asm volatile("mbarrier.arrive.expect_tx.shared::cta.b64 _, [%0], %1;" :: "r"(bar), "r"(bytes) : "memory"); }
__device__ __forceinline__ void mbar_arrive(uint32_t bar, uint32_t cnt) { asm volatile("mbarrier.arrive.shared::cta.b64 _, [%0], %1;" :: "r"(bar), "r"(cnt) : "memory"); }
__device__ __forceinline__ void mbar_wait(uint32_t bar, uint32_t parity) {
    uint32_t done; int it = 0;
    do {
        asm volatile("{\n.reg .pred p;\nmbarrier.try_wait.parity.shared::cta.b64 p, [%1], %2;\nselp.u32 %0, 1, 0, p;\n}"
                     : "=r"(done) : "r"(bar), "r"(parity) : "memory");
    } while (!done && ++it < MBAR_LIMIT);
}
__device__ __forceinline__ bool mbar_test(uint32_t bar, uint32_t parity) {
    uint32_t done;
    asm volatile("{\n.reg .pred p;\nmbarrier.test_wait.parity.shared::cta.b64 p, [%1], %2;\nselp.u32 %0, 1, 0, p;\n}"
                 : "=r"(done) : "r"(bar), "r"(parity) : "memory");
    return done != 0;
}
__device__ __forceinline__ void bulk_g2s(uint32_t dst, const void* src, uint32_t bytes, uint32_t bar) {
    uint64_t pol;
    asm("createpolicy.fractional.L2::evict_first.b64 %0, 1.0;" : "=l"(pol));
    asm volatile("cp.async.bulk.shared::cluster.global.mbarrier::complete_tx::bytes.L2::cache_hint [%0], [%1], %2, [%3], %4;"
                 :: "r"(dst), "l"(src), "r"(bytes), "r"(bar), "l"(pol) : "memory");
}
__device__ __forceinline__ void bulk_pf(const void* src, uint32_t bytes) {
    asm volatile("cp.async.bulk.prefetch.L2.global [%0], %1;" :: "l"(src), "r"(bytes) : "memory");
}
__device__ __forceinline__ void tma2d(uint32_t dst, const CUtensorMap* m, int c0, int c1, uint32_t bar) {
    asm volatile("cp.async.bulk.tensor.2d.shared::cluster.global.mbarrier::complete_tx::bytes [%0], [%1, {%3, %4}], [%2];"
                 :: "r"(dst), "l"(m), "r"(bar), "r"(c0), "r"(c1) : "memory");
}
__device__ __forceinline__ void tma3d(uint32_t dst, const CUtensorMap* m, int c0, int c1, int c2, uint32_t bar) {
    asm volatile("cp.async.bulk.tensor.3d.shared::cluster.global.mbarrier::complete_tx::bytes [%0], [%1, {%3, %4, %5}], [%2];"
                 :: "r"(dst), "l"(m), "r"(bar), "r"(c0), "r"(c1), "r"(c2) : "memory");
}
__device__ __forceinline__ uint32_t ldg32(const void* p) {
    uint32_t r;
    asm volatile("ld.global.nc.L1::no_allocate.u32 %0, [%1];" : "=r"(r) : "l"(p));
    return r;
}
__device__ __forceinline__ uint32_t lds32(uint32_t a) { uint32_t r; asm volatile("ld.shared.u32 %0, [%1];" : "=r"(r) : "r"(a) : "memory"); return r; }
__device__ __forceinline__ float ldsf(uint32_t a) { float r; asm volatile("ld.shared.f32 %0, [%1];" : "=f"(r) : "r"(a) : "memory"); return r; }
__device__ __forceinline__ void lds64(uint32_t& x, uint32_t& y, uint32_t a) {
    asm volatile("ld.shared.v2.u32 {%0,%1}, [%2];" : "=r"(x), "=r"(y) : "r"(a) : "memory");
}
__device__ __forceinline__ uint4 lds128(uint32_t a) {
    uint4 r;
    asm volatile("ld.shared.v4.u32 {%0,%1,%2,%3}, [%4];" : "=r"(r.x), "=r"(r.y), "=r"(r.z), "=r"(r.w) : "r"(a) : "memory");
    return r;
}
__device__ __forceinline__ float4 lds128f(uint32_t a) {
    float4 r;
    asm volatile("ld.shared.v4.f32 {%0,%1,%2,%3}, [%4];" : "=f"(r.x), "=f"(r.y), "=f"(r.z), "=f"(r.w) : "r"(a) : "memory");
    return r;
}
__device__ __forceinline__ void sts16(uint32_t a, uint32_t v) { asm volatile("st.shared.u16 [%0], %1;" :: "r"(a), "h"((unsigned short)v) : "memory"); }
__device__ __forceinline__ void sts32(uint32_t a, uint32_t v) { asm volatile("st.shared.u32 [%0], %1;" :: "r"(a), "r"(v) : "memory"); }
__device__ __forceinline__ void sts64f(uint32_t a, float x, float y) { asm volatile("st.shared.v2.f32 [%0], {%1,%2};" :: "r"(a), "f"(x), "f"(y) : "memory"); }
__device__ __forceinline__ void sts128f(uint32_t a, float x, float y, float z, float w) {
    asm volatile("st.shared.v4.f32 [%0], {%1,%2,%3,%4};" :: "r"(a), "f"(x), "f"(y), "f"(z), "f"(w) : "memory");
}
__device__ __forceinline__ void mma16816(float (&d)[4], uint32_t a0, uint32_t a1, uint32_t a2, uint32_t a3, uint32_t b0, uint32_t b1) {
    asm volatile("mma.sync.aligned.m16n8k16.row.col.f32.bf16.bf16.f32 {%0,%1,%2,%3}, {%4,%5,%6,%7}, {%8,%9}, {%0,%1,%2,%3};"
                 : "+f"(d[0]), "+f"(d[1]), "+f"(d[2]), "+f"(d[3]) : "r"(a0), "r"(a1), "r"(a2), "r"(a3), "r"(b0), "r"(b1));
}
__device__ __forceinline__ void mma_f(float (&d)[4], const uint32_t (&a)[4], uint32_t b0, uint32_t b1) { mma16816(d, a[0], a[1], a[2], a[3], b0, b1); }
__device__ __forceinline__ void ldsm4(uint32_t (&r)[4], uint32_t addr) {
    asm volatile("ldmatrix.sync.aligned.m8n8.x4.shared.b16 {%0,%1,%2,%3}, [%4];" : "=r"(r[0]), "=r"(r[1]), "=r"(r[2]), "=r"(r[3]) : "r"(addr) : "memory");
}
__device__ __forceinline__ void ldsm4t(uint32_t (&r)[4], uint32_t addr) {
    asm volatile("ldmatrix.sync.aligned.m8n8.x4.trans.shared.b16 {%0,%1,%2,%3}, [%4];" : "=r"(r[0]), "=r"(r[1]), "=r"(r[2]), "=r"(r[3]) : "r"(addr) : "memory");
}
__device__ __forceinline__ uint32_t pack_bf16(float lo, float hi) {
    uint32_t r;
    asm("cvt.rn.bf16x2.f32 %0, %1, %2;" : "=r"(r) : "f"(hi), "f"(lo));
    return r;
}
__device__ __forceinline__ float bf_lo(uint32_t w) { return __uint_as_float(w << 16); }
__device__ __forceinline__ float bf_hi(uint32_t w) { return __uint_as_float(w & 0xffff0000u); }
__device__ __forceinline__ float rbf(float x) { return __uint_as_float(pack_bf16(0.f, x)); }
__device__ __forceinline__ uint32_t mul2(uint32_t a, uint32_t b) { uint32_t r; asm("mul.rn.bf16x2 %0, %1, %2;" : "=r"(r) : "r"(a), "r"(b)); return r; }
__device__ __forceinline__ uint32_t add2(uint32_t a, uint32_t b) { uint32_t r; asm("add.rn.bf16x2 %0, %1, %2;" : "=r"(r) : "r"(a), "r"(b)); return r; }
__device__ __forceinline__ uint32_t sub2(uint32_t a, uint32_t b) { uint32_t r; asm("sub.rn.bf16x2 %0, %1, %2;" : "=r"(r) : "r"(a), "r"(b)); return r; }
__device__ __forceinline__ unsigned long long ld_relaxed64(const unsigned long long* p) {
    unsigned long long v;
    asm volatile("ld.relaxed.gpu.global.u64 %0, [%1];" : "=l"(v) : "l"(p) : "memory");
    return v;
}
__device__ __forceinline__ void st_relaxed64(unsigned long long* p, unsigned long long v) {
    asm volatile("st.relaxed.gpu.global.u64 [%0], %1;" :: "l"(p), "l"(v) : "memory");
}
__device__ __forceinline__ float4 ld_relaxed_f4(const float4* p) {
    float4 v;
    asm volatile("ld.relaxed.gpu.global.v4.f32 {%0,%1,%2,%3}, [%4];" : "=f"(v.x), "=f"(v.y), "=f"(v.z), "=f"(v.w) : "l"(p) : "memory");
    return v;
}
__device__ __forceinline__ void red_f4(float4* p, float a, float b, float c, float d) {
    asm volatile("red.relaxed.gpu.global.add.v4.f32 [%0], {%1,%2,%3,%4};" :: "l"(p), "f"(a), "f"(b), "f"(c), "f"(d) : "memory");
}
__device__ __forceinline__ float4 atom_f4(float4* p, float a, float b, float c, float d) {
    float4 v;
    asm volatile("atom.relaxed.gpu.global.add.v4.f32 {%0,%1,%2,%3}, [%4], {%5,%6,%7,%8};"
                 : "=f"(v.x), "=f"(v.y), "=f"(v.z), "=f"(v.w) : "l"(p), "f"(a), "f"(b), "f"(c), "f"(d) : "memory");
    return v;
}
__device__ __forceinline__ void cbar() { asm volatile("bar.sync 2, 256;" ::: "memory"); }
__device__ __forceinline__ unsigned long long* mod_ptr(int i) { return &g_mod[(i >> 4) * 128 + (i & 15)]; }
__device__ __forceinline__ int acc_idx(int i) { return (i >> 3) * 64 + ((i >> 2) & 1) * 16 + (i & 3); }
__device__ __forceinline__ bool has_tag(unsigned long long v, uint32_t tag) { return (uint32_t)(v >> 32) == tag; }

__device__ __forceinline__ void ln_partial(uint32_t w, uint32_t st, int warp, int lane) {
    const float a = bf_lo(w), b = bf_hi(w);
    float s = a + b, m = (a - b) * (a - b) * 0.5f;
#pragma unroll
    for (int o = 1; o <= 16; o <<= 1) {
        const float so = __shfl_xor_sync(0xffffffffu, s, o), mo = __shfl_xor_sync(0xffffffffu, m, o);
        const float d = s - so;
        s += so;
        m = fmaf(d * d, 0.25f / o, m + mo);
    }
    if (lane == 0) sts64f(st + 8 * warp, s, m);
}
__device__ __forceinline__ void ln_final(const float4& q0, const float4& q1, const float4& q2, const float4& q3, uint32_t& mean2, float& inv_den) {
    const float m2 = ((q0.y + q0.w) + (q1.y + q1.w)) + ((q2.y + q2.w) + (q3.y + q3.w));
    const float e1 = q0.z - q0.x, e2 = q1.x - q0.x, e3 = q1.z - q0.x, e4 = q2.x - q0.x, e5 = q2.z - q0.x, e6 = q3.x - q0.x, e7 = q3.z - q0.x;
    const float t1 = ((e1 + e2) + (e3 + e4)) + ((e5 + e6) + e7);
    const float t2 = (fmaf(e1, e1, e2 * e2) + fmaf(e3, e3, e4 * e4)) + fmaf(e7, e7, fmaf(e5, e5, e6 * e6));
    const float var = rbf(fmaf(fmaf(t1 * -0.125f, t1, t2), 1.0f / 32768.0f, m2 * (1.0f / 512.0f)));
    const float mean = fmaf(t1, 1.0f / 512.0f, q0.x * (1.0f / 64.0f));
    mean2 = pack_bf16(mean, mean);
    const float ve = rbf(var + 1e-5f);
    float rs;
    asm("rsqrt.approx.ftz.f32 %0, %1;" : "=f"(rs) : "f"(ve));
    const float e = fmaf(-rbf(ve * rs), rs, 1.0f);
    inv_den = fmaf(fmaf(e, e, e), rs, rs);
}
__device__ __forceinline__ uint32_t ln_mod(uint32_t w, uint32_t mean2, float inv_den, uint32_t onep, uint32_t shift) {
    const uint32_t d = sub2(w, mean2);
    return add2(mul2(pack_bf16(bf_lo(d) * inv_den, bf_hi(d) * inv_den), onep), shift);
}
__device__ __forceinline__ uint32_t residual(uint32_t xw, uint32_t gate, float a0, float a1) {
    return add2(xw, mul2(gate, pack_bf16(a0, a1)));
}
__device__ __forceinline__ void load_frag_pair(uint32_t (&X)[4], uint32_t (&Y)[4], uint32_t a0, uint32_t a1) {
    lds64(X[0], X[1], a0); lds64(X[2], X[3], a1);
    lds64(Y[0], Y[1], a0 ^ 64); lds64(Y[2], Y[3], a1 ^ 64);
}
#define ONE2 0x3f803f80u

__global__ void __launch_bounds__(NTHREADS, 1) fused_decode_kernel(const __grid_constant__ Params p) {
    extern __shared__ __align__(1024) unsigned char smem[];
    const int tid = threadIdx.x, cta = blockIdx.x;
    if (tid == 0) {
        bulk_pf((const char*)p.k + (size_t)cta * (16 * UNIT_BYTES) + UNIT_BYTES, UNIT_BYTES / 2);
        bulk_pf((const char*)p.k + (size_t)cta * (16 * UNIT_BYTES) + UNIT_BYTES + UNIT_BYTES / 2, UNIT_BYTES / 2);
    }
    uint32_t sb = smem_u32(smem);
    asm volatile("" : "+r"(sb));
    const int warp = tid >> 5, lane = tid & 31, head = cta >> 2;
    const int ffn = cta - cta / 3;
    const bool is_ffn = cta % 3 != 2;
    const uint32_t bar_full = sb + SM_BAR, bar_empty = bar_full + 8 * SLOTS;
    const uint32_t bar_mod = bar_empty + 8 * SLOTS, bar_gu = bar_mod + 8, bar_aux = bar_mod + 16, bar_wd = bar_mod + 24, bar_go = bar_mod + 32;
    const uint32_t bar_trig = bar_mod + 40;

    if (warp < 8) {
        asm volatile("setmaxnreg.inc.sync.aligned.u32 232;");
        const int g = lane >> 2, t = lane & 3;
        const uint32_t cw = ldg32(p.c + 2 * tid);
        const uint32_t xw = ldg32(p.x + 2 * tid);
        if (tid == 0) {
            uint32_t epoch;
            asm volatile("ld.relaxed.gpu.global.u32 %0, [%1];" : "=r"(epoch) : "l"(&g_epoch) : "memory");
            sts32(sb + SM_ML + 8, epoch + 1);
        }
        const uint32_t zero = p.zero;
        const uint32_t selLo = (g & 1) ? 0x1044u : 0x4410u;
        const uint32_t selHi = (g & 1) ? 0x3244u : 0x4432u;
        const uint32_t fo0 = 2 * t * 128 + (((g >> 1) ^ (2 * t)) << 4) + (g & 1) * 8;
        const uint32_t fo1 = (2 * t + 1) * 128 + (((g >> 1) ^ (2 * t + 1)) << 4) + (g & 1) * 8;
        uint32_t W[32][4];
        uint32_t mean2;
        float inv_den;
        sts32(sb + SM_TV + 16 * tid, xw);
        ln_partial(xw, sb + SM_ST, warp, lane);
        asm volatile("bar.sync 1, 384;" ::: "memory");
        const uint32_t tag = lds32(sb + SM_ML + 8);
        ln_final(lds128f(sb + SM_ST), lds128f(sb + SM_ST + 16), lds128f(sb + SM_ST + 32), lds128f(sb + SM_ST + 48), mean2, inv_den);

        {
            const float c0 = bf_lo(cw), c1 = bf_hi(cw);
            const uint32_t sw = pack_bf16(__fdividef(c0, 1.0f + __expf(-c0)), __fdividef(c1, 1.0f + __expf(-c1)));
            const uint32_t a = sb + SM_GU + (64 * warp + (lane & 7) + 8 * (lane >> 4)) * 48 + ((lane >> 3) & 1) * 16;
            const uint32_t a2 = sb + SM_GU + (64 * warp + lane) * 48 + 32;
            float m0[4] = {0.f, 0.f, 0.f, 0.f}, m1[4] = {0.f, 0.f, 0.f, 0.f};
            mbar_wait(bar_mod, 0);
#pragma unroll
            for (int j = 0; j < 4; j += 2) {
                uint32_t f0[4], f1[4], f2[4];
                ldsm4t(f0, a + j * 768); ldsm4t(f1, a + j * 768 + 768); ldsm4t(f2, a2 + j * 768);
                const uint32_t b0 = __shfl_sync(0xffffffffu, sw, 8 * j + t), b1 = __shfl_sync(0xffffffffu, sw, 8 * j + 4 + t);
                const uint32_t b2 = __shfl_sync(0xffffffffu, sw, 8 * j + 8 + t), b3 = __shfl_sync(0xffffffffu, sw, 8 * j + 12 + t);
                mma_f(m0, f0, b0, b1);
                mma16816(m1, f2[0], 0u, f2[1], 0u, b0, b1);
                mma_f(m0, f1, b2, b3);
                mma16816(m1, f2[2], 0u, f2[3], 0u, b2, b3);
            }
            if (t == 0) sts128f(sb + SM_R3 + (warp * 8 + g) * 16, m0[0], m0[2], m1[0], 0.f);
            cbar();
            if (warp == 0) {
                float s = 0.f;
#pragma unroll
                for (int w = 0; w < 8; w++) s += ldsf(sb + SM_R3 + w * 128 + lane * 4);
                const float s2 = __shfl_down_sync(0xffffffffu, s, 4);
                if (t < 3 && !(g & 1))
                    st_relaxed64(mod_ptr(12 * cta + 4 * t + (g >> 1)), ((unsigned long long)tag << 32) | pack_bf16(s, s2));
            }
        }
        {
            mbar_wait(bar_full + 8 * (warp & 4), 0);
            const uint32_t a = sb + SM_RING + (warp >> 2) * 65536 + (warp & 3) * 8192;
            uint32_t dep = 0;
#pragma unroll
            for (int s = 0; s < 16; s++) {
                const uint32_t as = a + (s >> 3) * 32768 + (s & 7) * 1024;
                load_frag_pair(W[2 * s], W[2 * s + 1], as + fo0, as + fo1);
                dep |= W[2 * s][0] | W[2 * s][2] | W[2 * s + 1][0] | W[2 * s + 1][2];
            }
            dep = __reduce_or_sync(0xffffffffu, dep & zero);
            if (lane < 2) mbar_arrive(bar_empty + 8 * ((warp & 4) + 2 * lane + ((warp >> 1) & 1)) + dep, 4);
        }
        {
            unsigned long long va, vc; int it = 0;
            while (true) {
                va = ld_relaxed64(mod_ptr(tid)); vc = ld_relaxed64(mod_ptr(256 + tid));
                if (__all_sync(0xffffffffu, has_tag(va, tag) && has_tag(vc, tag)) || ++it >= SPIN_LIMIT) break;
                __nanosleep(MOD_SLEEP);
            }
            const uint32_t hw = ln_mod(xw, mean2, inv_den, add2(ONE2, (uint32_t)vc), (uint32_t)va);
            float qa[4][4];
#pragma unroll
            for (int i = 0; i < 4; i++) { qa[i][0] = qa[i][1] = qa[i][2] = qa[i][3] = 0.f; }
#pragma unroll
            for (int s = 0; s < 8; s++) {
                const uint32_t w0 = __shfl_sync(0xffffffffu, hw, 4 * s + t);
                const uint32_t b0 = __byte_perm(w0, 0u, selLo), b1 = __byte_perm(w0, 0u, selHi);
                mma_f(qa[0], W[2 * s], b0, b1);
                mma_f(qa[1], W[2 * s + 1], b0, b1);
                mma_f(qa[2], W[2 * s + 16], b0, b1);
                mma_f(qa[3], W[2 * s + 17], b0, b1);
            }
            if (t == 0) {
#pragma unroll
                for (int i = 0; i < 4; i++) sts128f(sb + SM_RED + warp * 512 + i * 128 + g * 16, qa[i][0], qa[i][1], qa[i][2], qa[i][3]);
            }
            cbar();
            if (tid < 128) {
                float s = 0.f;
#pragma unroll
                for (int w = 0; w < 8; w++) s += ldsf(sb + SM_RED + w * 512 + tid * 4);
                sts16(sb + SM_VEC + 2 * tid, pack_bf16(s, 0.f));
            }
            cbar();
        }
        if (tid == 0) mbar_arrive(bar_trig + 8, 1);
        uint32_t pw[8];
#pragma unroll
        for (int i = 0; i < 8; i++) pw[i] = 0u;
        {
            uint32_t qf[16];
#pragma unroll
            for (int j = 0; j < 16; j++) qf[j] = lds32(sb + SM_VEC + ((j ^ g) << 4) + 4 * t);
            const uint32_t lrow = (lane & 7) + 8 * ((lane >> 3) & 1);
            const uint32_t loff = (warp & 3) * 4096 + lrow * 256 + (((lane >> 4) ^ (lane & 7)) << 4);
            int slot = (U_K + (warp >> 2)) % SLOTS, ph = ((U_K + (warp >> 2)) / SLOTS) & 1;
#pragma unroll 1
            for (int n = 0; n < 8; n++) {
                mbar_wait(bar_full + 8 * slot, ph);
                const uint32_t a = sb + SM_RING + slot * UNIT_BYTES + loff;
                float c0[4] = {0.f, 0.f, 0.f, 0.f}, c1[4] = {0.f, 0.f, 0.f, 0.f};
#pragma unroll
                for (int j = 0; j < 8; j += 2) {
                    uint32_t f0[4], f1[4];
                    ldsm4(f0, a ^ (32 * j));
                    ldsm4(f1, a ^ (32 * j + 32));
                    mma_f(c0, f0, qf[2 * j], qf[2 * j + 1]);
                    mma_f(c1, f1, qf[2 * j + 2], qf[2 * j + 3]);
                }
                const float slo = (g & 1) ? c0[1] + c1[1] : c0[0] + c1[0];
                const float shi = (g & 1) ? c0[3] + c1[3] : c0[2] + c1[2];
                uint32_t r = pack_bf16(slo, shi);
                if (lane == 0) mbar_arrive(bar_empty + 8 * slot + (r & zero), 2);
                r = pack_bf16(bf_lo(r) * 0.08838834764831845f, bf_hi(r) * 0.08838834764831845f);
#pragma unroll
                for (int i = 0; i < 7; i++) pw[i] = pw[i + 1];
                pw[7] = r;
                slot += n < 4 ? 2 : 4; if (slot >= SLOTS) { slot -= SLOTS; ph ^= 1; }
                if (n == 4 + (warp >> 1)) {
                    const int u = U_WO + 4 * (warp >> 1) + (warp & 1), ws = u % SLOTS;
                    mbar_wait(bar_full + 8 * ws, (u / SLOTS) & 1);
                    const uint32_t wa = sb + SM_RING + ws * UNIT_BYTES;
                    uint32_t dep = 0;
#pragma unroll
                    for (int s = 0; s < 16; s++) {
                        const uint32_t as = wa + ((s * 1024 + (cta & 3) * 4096) & 16383);
                        load_frag_pair(W[2 * s], W[2 * s + 1], as + fo0, as + fo1);
                        dep |= W[2 * s][0] | W[2 * s][2] | W[2 * s + 1][0] | W[2 * s + 1][2];
                    }
                    dep = __reduce_or_sync(0xffffffffu, dep & zero);
                    if (lane == 0) mbar_arrive(bar_empty + 8 * ws + dep, 8);
                }
            }
        }
        if (tid == 0) mbar_arrive(bar_trig, 1);
        float mw;
        {
            const bool valid = (t == (g >> 1));
            if (valid) st_relaxed64(&g_ls[(cta * 8 + warp) * 8 + g], ((unsigned long long)tag << 32) | pw[7]);
            mw = -INFINITY;
#pragma unroll
            for (int i = 0; i < 8; i++) mw = fmaxf(mw, fmaxf(bf_lo(pw[i]), bf_hi(pw[i])));
            if (!valid) mw = -INFINITY;
#pragma unroll
            for (int o = 16; o > 0; o >>= 1) mw = fmaxf(mw, __shfl_xor_sync(0xffffffffu, mw, o));
            float lw = 0.f;
#pragma unroll
            for (int i = 0; i < 8; i++) {
                const float e0 = valid ? __expf(bf_lo(pw[i]) - mw) : 0.f, e1 = valid ? __expf(bf_hi(pw[i]) - mw) : 0.f;
                lw += e0 + e1;
                pw[i] = pack_bf16(e0, e1);
            }
#pragma unroll
            for (int o = 16; o > 0; o >>= 1) lw += __shfl_xor_sync(0xffffffffu, lw, o);
            if (lane < 2)
                st_relaxed64(&g_stat[(cta * 8 + warp) * 2 + lane], ((unsigned long long)tag << 32) | __float_as_uint(lane ? lw : mw));
        }
        float acc[8][4];
#pragma unroll
        for (int i = 0; i < 8; i++) { acc[i][0] = acc[i][1] = acc[i][2] = acc[i][3] = 0.f; }
        float scale = 0.f;
        const int pl = 16 * (t >> 1) + 2 * g + (t & 1);
        float4* redp = &g_acc[acc_idx(32 * warp + pl)];
        asm volatile("" : "+l"(redp));
        float4* const pollp = redp;
        float4 v;
        {
            const uint32_t lrow = (lane & 7) + 8 * (lane >> 4);
            const uint32_t loff = (warp & 3) * 4096 + lrow * 256 + ((((lane >> 3) & 1) ^ (lane & 7)) << 4);
            int slot = (U_V + (warp >> 2)) % SLOTS, ph = ((U_V + (warp >> 2)) / SLOTS) & 1;
#pragma unroll 1
            for (int n = 0; n < 7; n++) {
                if (n == 2 && tid == 0) mbar_arrive(bar_trig + 16, 1);
                if (n == 6) {
                    mbar_wait(bar_aux, 0);
                    scale = __expf(mw - ldsf(sb + SM_ML)) * ldsf(sb + SM_ML + 4);
                }
                const uint32_t b0 = __byte_perm(pw[0], 0u, selLo), b1 = __byte_perm(pw[0], 0u, selHi);
#pragma unroll
                for (int i = 0; i < 6; i++) pw[i] = pw[i + 1];
                mbar_wait(bar_full + 8 * slot, ph);
                const uint32_t a = sb + SM_RING + slot * UNIT_BYTES + loff;
                uint32_t dep = 0;
#pragma unroll
                for (int c = 0; c < 8; c++) {
                    uint32_t f[4];
                    ldsm4t(f, a ^ (32 * c));
                    mma_f(acc[c], f, b0, b1);
                    dep |= f[0];
                }
                if (lane == 0) mbar_arrive(bar_empty + 8 * slot + (dep & zero), 2);
                slot += 2; if (slot >= SLOTS) { slot -= SLOTS; ph ^= 1; }
            }
        }
        {
            float e[8], f[8];
#pragma unroll
            for (int c = 0; c < 8; c++) { e[c] = acc[c][0] + acc[c][3]; f[c] = acc[c][1] + acc[c][2]; }
            float e2[4], f2[4];
#pragma unroll
            for (int c = 0; c < 8; c += 2) {
                e2[c >> 1] = e[c] + __shfl_xor_sync(0xffffffffu, e[c + 1], 1);
                f2[c >> 1] = f[c] + __shfl_xor_sync(0xffffffffu, f[c + 1], 1);
            }
            const float o0 = e2[0] + __shfl_xor_sync(0xffffffffu, e2[1], 2);
            const float o1 = f2[0] + __shfl_xor_sync(0xffffffffu, f2[1], 2);
            const float o2 = e2[2] + __shfl_xor_sync(0xffffffffu, e2[3], 2);
            const float o3 = f2[2] + __shfl_xor_sync(0xffffffffu, f2[3], 2);
            sts128f(sb + SM_RED + tid * 16, o0 * scale, o1 * scale, o2 * scale, o3 * scale);
            cbar();
            if (tid < 128) {
                const uint32_t rp = sb + SM_RED + tid * 4;
                const float s = ((ldsf(rp) + ldsf(rp + 512)) + (ldsf(rp + 1024) + ldsf(rp + 1536))) +
                                ((ldsf(rp + 2048) + ldsf(rp + 2560)) + (ldsf(rp + 3072) + ldsf(rp + 3584)));
                const int comp = tid & 3, tt = (tid >> 2) & 3, gg = tid >> 4;
                const int sidx = (8 * (comp >> 1) + 2 * tt + (comp & 1) - 4 * (cta & 3)) & 15;
                sts16(sb + SM_VEC + 2 * ((gg >> 1) * 32 + 2 * sidx + (gg & 1)), pack_bf16(s, 0.f));
            }
            cbar();
            uint4 ov[4];
#pragma unroll
            for (int i = 0; i < 4; i++) ov[i] = lds128(sb + SM_VEC + 64 * t + 16 * i);
            const uint32_t* ow = reinterpret_cast<const uint32_t*>(ov);
#pragma unroll
            for (int i = 0; i < 8; i++) { acc[i][0] = acc[i][1] = acc[i][2] = acc[i][3] = 0.f; }
#pragma unroll
            for (int s = 0; s < 16; s++) {
                const uint32_t b0 = __byte_perm(ow[s], 0u, selLo), b1 = __byte_perm(ow[s], 0u, selHi);
                mma_f(acc[2 * (s & 3)], W[2 * s], b0, b1);
                mma_f(acc[2 * (s & 3) + 1], W[2 * s + 1], b0, b1);
            }
#pragma unroll
            for (int i = 0; i < 4; i++) {
                acc[0][i] = (acc[0][i] + acc[2][i]) + (acc[4][i] + acc[6][i]);
                acc[1][i] = (acc[1][i] + acc[3][i]) + (acc[5][i] + acc[7][i]);
                acc[2][i] = acc[3][i] = acc[4][i] = acc[5][i] = acc[6][i] = acc[7][i] = 0.f;
            }
        }
        const uint4 tv = lds128(sb + SM_TV + 16 * (32 * warp + pl));
        const uint32_t gb = lds32(sb + SM_GB + 4 * (32 * warp + pl));
        uint32_t* outp = reinterpret_cast<uint32_t*>(p.out) + 32 * warp + pl;
        asm volatile("" : "+l"(outp));
        const uint32_t bvw = sb + SM_BV + warp * 576 + ((pl & 3) * 8 + 2 * (pl >> 3) + ((pl >> 2) & 1)) * 4;
        const uint32_t bvr = sb + SM_BV + warp * 576 + (g & 3) * 144 + t * 32;
        sts32(bvw + 288, tv.z); sts32(bvw + 432, tv.w);
        uint32_t agu = sb + SM_GU + (64 * warp + (lane & 7) + 8 * (lane >> 4)) * 32 + ((((lane >> 3) ^ (lane >> 2)) & 1) << 4);
        uint32_t ad0 = sb + SM_WD + warp * 2048 + fo0, ad1 = sb + SM_WD + warp * 2048 + fo1, ad2 = ad0 ^ 64, ad3 = ad1 ^ 64;
        uint32_t ars = (t & 1) ? sb + SM_RED + 1024 + warp * 256 + (4 * g + (t & 2)) * 8 : sb + SM_RED + warp * 128 + (4 * g + t) * 4;
        asm volatile("" : "+r"(agu), "+r"(ad0), "+r"(ad1), "+r"(ad2), "+r"(ad3), "+r"(ars));
        {
            uint32_t pb[8];
#pragma unroll
            for (int i = 0; i < 8; i++) pb[i] = lds32(sb + SM_PL + (32 * warp + 4 * i + t) * 4);
            const int lu = NUNIT - 2 + (warp >> 2);
            const uint32_t la = sb + SM_RING + (lu % SLOTS) * UNIT_BYTES + (warp & 3) * 4096 + ((lane & 7) + 8 * (lane >> 4)) * 64 +
                                ((((lane >> 3) & 1) ^ ((lane & 7) >> 1)) << 4);
            mbar_wait(bar_full + 8 * (lu % SLOTS), (lu / SLOTS) & 1);
#pragma unroll
            for (int ks = 0; ks < 4; ks++) {
                uint32_t f0[4], f1[4];
                ldsm4t(f0, la + ks * 1024); ldsm4t(f1, (la + ks * 1024) ^ 32);
                mma_f(acc[4 + (ks & 1)], f0, pb[2 * ks], pb[2 * ks + 1]);
                mma_f(acc[6 + (ks & 1)], f1, pb[2 * ks], pb[2 * ks + 1]);
            }
            if (t == 0) sts128f(sb + SM_R3 + (warp * 8 + g) * 16, acc[4][0] + acc[5][0], acc[4][2] + acc[5][2], acc[6][0] + acc[7][0], acc[6][2] + acc[7][2]);
            cbar();
            const uint32_t rp = sb + SM_R3 + 4 * lane;
            const uint32_t ol = pack_bf16(((ldsf(rp) + ldsf(rp + 128)) + (ldsf(rp + 256) + ldsf(rp + 384))) +
                                          ((ldsf(rp + 512) + ldsf(rp + 640)) + (ldsf(rp + 768) + ldsf(rp + 896))), 0.f);
#pragma unroll
            for (int s = 0; s < 4; s++) {
                const uint32_t b0 = __byte_perm(__shfl_sync(0xffffffffu, ol, 8 * t + s), 0u, selLo);
                const uint32_t b1 = __byte_perm(__shfl_sync(0xffffffffu, ol, 8 * t + 4 + s), 0u, selLo);
                mma_f(acc[2 * (s & 1)], W[2 * s], b0, b1);
                mma_f(acc[2 * (s & 1) + 1], W[2 * s + 1], b0, b1);
            }
            float X[4];
#pragma unroll
            for (int i = 0; i < 4; i++) X[i] = (t & 2) ? acc[1][i] + acc[3][i] : acc[0][i] + acc[2][i];
            const float a0 = (t & 1) ? X[2] : X[0], a1 = (t & 1) ? X[3] : X[1];
            if (is_ffn) {
                v = atom_f4(redp, a0, a1, 1.0f, 0.0f);
                v.x += a0; v.y += a1; v.z += 1.0f;
            } else {
                red_f4(redp, a0, a1, 1.0f, 0.0f);
                v = make_float4(0.f, 0.f, 0.f, 0.f);
            }
        }
        if (is_ffn) {
            uint32_t fg[4][4], fu[4][4], fd[4][4];
            bool have_gu = false;
#define LOAD_GU() do { \
                _Pragma("unroll") for (int j = 0; j < 4; j++) { ldsm4t(fg[j], agu + j * 512); ldsm4t(fu[j], agu + 16384 + j * 512); } \
                have_gu = true; } while (0)
#define LOAD_WD() do { lds64(fd[0][0], fd[0][1], ad0); lds64(fd[0][2], fd[0][3], ad1); lds64(fd[1][0], fd[1][1], ad2); lds64(fd[1][2], fd[1][3], ad3); \
                lds64(fd[2][0], fd[2][1], ad0 + 1024); lds64(fd[2][2], fd[2][3], ad1 + 1024); lds64(fd[3][0], fd[3][1], ad2 + 1024); lds64(fd[3][2], fd[3][3], ad3 + 1024); } while (0)
#define TRY_GU() do { if (!have_gu && mbar_test(bar_gu, 0)) LOAD_GU(); } while (0)
            int it = 0;
            while (true) {
                if (it > 0) {
                    const uint32_t c0 = clock32(), w = min((uint32_t)((float)NCTA - __shfl_sync(0xffffffffu, v.z, 0)), (uint32_t)NCTA) * POLL_K;
                    while (clock32() - c0 < w) { }
                    v = ld_relaxed_f4(pollp);
                }
                TRY_GU();
                if (__all_sync(0xffffffffu, v.z == (float)NCTA) || ++it >= SPIN_LIMIT) break;
            }
            const uint32_t yw = residual(tv.x, tv.y, v.x, v.y);
            if (!have_gu) { mbar_wait(bar_gu, 0); LOAD_GU(); }
            float s;
            {
                const float ya = bf_lo(yw), yb = bf_hi(yw);
                const uint32_t zh = mul2(yw, tv.z);
                sts32(bvw, zh);
                sts32(bvw + 144, pack_bf16(fmaf(ya, bf_lo(tv.z), -bf_lo(zh)), fmaf(yb, bf_hi(tv.z), -bf_hi(zh))));
                float ls = ya + yb, lm = (ya - yb) * (ya - yb) * 0.5f, so, mo, d;
#define LN_ROUND(o) so = __shfl_xor_sync(0xffffffffu, ls, o); mo = __shfl_xor_sync(0xffffffffu, lm, o); d = ls - so; ls += so; lm = fmaf(d * d, 0.25f / o, lm + mo)
                __syncwarp();
                LN_ROUND(1);
                const uint4 bA = lds128(bvr), bB = lds128(bvr + 16);
                LN_ROUND(2);
                float cg[2][4], cu[2][4];
#pragma unroll
                for (int i = 0; i < 4; i++) { cg[0][i] = cg[1][i] = cu[0][i] = cu[1][i] = 0.f; }
                mma_f(cg[0], fg[0], bA.x, bA.y); mma_f(cu[0], fu[0], bA.x, bA.y);
                mma_f(cg[1], fg[1], bA.z, bA.w); mma_f(cu[1], fu[1], bA.z, bA.w);
                LN_ROUND(4);
                mma_f(cg[0], fg[2], bB.x, bB.y); mma_f(cu[0], fu[2], bB.x, bB.y);
                mma_f(cg[1], fg[3], bB.z, bB.w); mma_f(cu[1], fu[3], bB.z, bB.w);
                LN_ROUND(8);
                LN_ROUND(16);
                float r[4];
#pragma unroll
                for (int i = 0; i < 4; i++) r[i] = (t & 2) ? cu[0][i] + cu[1][i] : cg[0][i] + cg[1][i];
                if (t & 1) sts128f(ars, r[0], r[1], r[2], r[3]);
                else sts64f(ars, r[0] + r[1], r[2] + r[3]);
                if (lane == 0) sts64f(sb + SM_ST + 64 + 8 * warp, ls, lm);
                mbar_wait(bar_wd, 0);
                LOAD_WD();
                cbar();
                const float4 q0 = lds128f(sb + SM_ST + 64), q1 = lds128f(sb + SM_ST + 80), q2 = lds128f(sb + SM_ST + 96), q3 = lds128f(sb + SM_ST + 112);
                const uint32_t rp = sb + SM_RED + 4 * lane;
                const float r0 = ldsf(rp), r1 = ldsf(rp + 128), r2 = ldsf(rp + 256), r3 = ldsf(rp + 384);
                const float r4 = ldsf(rp + 512), r5 = ldsf(rp + 640), r6 = ldsf(rp + 768), r7 = ldsf(rp + 896);
                uint32_t bb[8], cc[8];
#pragma unroll
                for (int w = 0; w < 8; w++) lds64(bb[w], cc[w], sb + SM_RED + 1024 + w * 256 + 8 * lane);
#define F_(x) __uint_as_float(x)
                const float vb = ((F_(bb[0]) + F_(bb[1])) + (F_(bb[2]) + F_(bb[3]))) + ((F_(bb[4]) + F_(bb[5])) + (F_(bb[6]) + F_(bb[7])));
                const float vc = ((F_(cc[0]) + F_(cc[1])) + (F_(cc[2]) + F_(cc[3]))) + ((F_(cc[4]) + F_(cc[5])) + (F_(cc[6]) + F_(cc[7])));
                ln_final(q0, q1, q2, q3, mean2, inv_den);
                s = rbf(fmaf(fmaf(-bf_lo(mean2), vb, ((r0 + r1) + (r2 + r3)) + ((r4 + r5) + (r6 + r7))), inv_den, vc));
            }
            const uint32_t hh = pack_bf16(s * __shfl_xor_sync(0xffffffffu, s, 2), 0.f);
            uint32_t b[4];
#pragma unroll
            for (int i = 0; i < 4; i++) b[i] = __byte_perm(__shfl_sync(0xffffffffu, hh, 8 * t + 4 * (i & 1) + (i >> 1)), 0u, selLo);
            float X[4] = {0.f, 0.f, 0.f, 0.f}, Y[4] = {0.f, 0.f, 0.f, 0.f}, X2[4] = {0.f, 0.f, 0.f, 0.f}, Y2[4] = {0.f, 0.f, 0.f, 0.f};
            mma_f(X, fd[0], b[0], b[1]);
            mma_f(Y, fd[1], b[0], b[1]);
            mma_f(X2, fd[2], b[2], b[3]);
            mma_f(Y2, fd[3], b[2], b[3]);
#pragma unroll
            for (int i = 0; i < 4; i++) { const float xa = X[i] + X2[i], ya = Y[i] + Y2[i]; X[i] = (t & 2) ? ya : xa; }
            const float v0 = (t & 1) ? X[2] : X[0], v1 = (t & 1) ? X[3] : X[1];
            const float4 old = atom_f4(redp + ACC2_OFF, v0, v1, 1.0f, 0.0f);
            if (old.z == (float)(NFFN - 1))
                asm volatile("st.global.u32 [%0], %1;" :: "l"(outp), "r"(residual(yw, gb, old.x + v0, old.y + v1)) : "memory");
        }
    } else {
        asm volatile("setmaxnreg.dec.sync.aligned.u32 40;");
        if (tid == 256) {
            mbar_init(bar_mod, 1);
            mbar_init(bar_full, 1);
            mbar_init(bar_full + 8 * 4, 1);
            asm volatile("fence.mbarrier_init.release.cluster;" ::: "memory");
            mbar_expect_tx(bar_mod, 24576);
            tma2d(sb + SM_GU, &p.m_mod, 24 * cta, 0, bar_mod);
            tma2d(sb + SM_GU + 12288, &p.m_mod, 24 * cta, 256, bar_mod);
            mbar_expect_tx(bar_full, 65536);
            tma3d(sb + SM_RING, &p.m_wq, 0, 0, 2 * head, bar_full);
            mbar_expect_tx(bar_full + 8 * 4, 65536);
            tma3d(sb + SM_RING + 65536, &p.m_wq, 0, 256, 2 * head, bar_full + 8 * 4);
        } else if (tid == 288) {
            mbar_init(bar_full + 8 * U_K, 1);
            asm volatile("fence.mbarrier_init.release.cluster;" ::: "memory");
            mbar_expect_tx(bar_full + 8 * U_K, UNIT_BYTES);
            bulk_g2s(sb + SM_RING + U_K * UNIT_BYTES, (const char*)p.k + (size_t)cta * (16 * UNIT_BYTES), UNIT_BYTES, bar_full + 8 * U_K);
#pragma unroll
            for (int s = 0; s < SLOTS; s++) {
                if (s != 0 && s != 4 && s != U_K) mbar_init(bar_full + 8 * s, 1);
                mbar_init(bar_empty + 8 * s, 8);
            }
            mbar_init(bar_gu, 2); mbar_init(bar_aux, 2); mbar_init(bar_wd, 1); mbar_init(bar_go, 1);
            mbar_init(bar_trig, 1); mbar_init(bar_trig + 8, 1); mbar_init(bar_trig + 16, 1);
            asm volatile("fence.mbarrier_init.release.cluster;" ::: "memory");
#pragma unroll
            for (int s = 1; s < U_K; s++) if (s != 4) mbar_arrive(bar_full + 8 * s, 1);
        }
        const uint32_t t_start = gtime32();
        __syncwarp();
        asm volatile("bar.sync 1, 384;" ::: "memory");
        if (warp == 8) {
            if (lane == 0) {
                const char* kb = (const char*)p.k + (size_t)cta * (16 * UNIT_BYTES);
                const char* vb = (const char*)p.v + (size_t)cta * (16 * UNIT_BYTES) - 18 * UNIT_BYTES;
                const char* ob = (const char*)p.wo + (size_t)cta * (2 * UNIT_BYTES) - 4 * UNIT_BYTES;
                constexpr int U0 = U_K + 1;
                uint32_t slot = U0 % SLOTS, ph = ((U0 / SLOTS) & 1) ^ 1;
                uint32_t sa = (U0 - WMAX) % SLOTS, pa = ((U0 - WMAX) / SLOTS) & 1;
                uint32_t sn = (U0 - WMIN) % SLOTS, pn = ((U0 - WMIN) / SLOTS) & 1;
                const uint32_t t_base = t_start + T_A;
                uint32_t now = t_start;
                int pj = 2;
                int j = 1, wo = 0;
#pragma unroll 1
                for (int u = U0; u < NUNIT; u++) {
                    const bool is_wo = (u >= U_WO && u < U_V && !((u - U_WO) & 2));
#pragma unroll 1
                    for (int it = 0; it < SPIN_LIMIT; it++) {
                        const bool calm = u - WMAX < U_K || mbar_test(bar_full + 8 * sa, pa);
                        const bool ok = calm && (u < SLOTS || mbar_test(bar_empty + 8 * slot, ph));
                        if (ok && (is_wo || pj > j)) break;
                        if ((int)(now - (t_base + pj * TAU)) >= 0 || (ok && u - WMIN >= U_K && mbar_test(bar_full + 8 * sn, pn))) {
                            if (ok && pj == j) { pj++; break; }
                            if (calm && pj < j + PFMAX && pj < 34) {
                                bulk_pf((pj < 4 ? kb : (pj < 6 ? ob : (pj < 18 ? kb - 2 * UNIT_BYTES : vb))) + (size_t)pj * UNIT_BYTES, UNIT_BYTES);
                                pj++;
                                continue;
                            }
                        }
                        now = gtime32();
                    }
                    const uint32_t dst = sb + SM_RING + slot * UNIT_BYTES, bar = bar_full + 8 * slot;
                    mbar_expect_tx(bar, UNIT_BYTES);
                    if (is_wo) { tma3d(dst, &p.m_wo, 0, head * 128, wo, bar); wo++; }
                    else if (u >= NUNIT - 2) {
                        const int row = head * 4096 + (u - (NUNIT - 2)) * 2048 + 896;
                        tma2d(dst, &p.m_v, 32 * (cta & 3), row, bar);
                        tma2d(dst + 8192, &p.m_v, 32 * (cta & 3), row + 1024, bar);
                        j++;
                    } else {
                        bulk_g2s(dst, (j < 4 ? kb : (j < 18 ? kb - 2 * UNIT_BYTES : vb)) + (size_t)j * UNIT_BYTES, UNIT_BYTES, bar);
                        j += (j == 3) ? 3 : 1;
                    }
                    if (++slot == SLOTS) { slot = 0; ph ^= 1; }
                    if (++sa == SLOTS) { sa = 0; pa ^= 1; }
                    if (++sn == SLOTS) { sn = 0; pn ^= 1; }
                }
                if (is_ffn) {
                    mbar_expect_tx(bar_wd, 16384);
#pragma unroll 1
                    for (int it = 0; it < SPIN_LIMIT; it++)
                        if ((int)(gtime32() - (t_start + (uint32_t)(T_A + 34 * TAU + GU_DELAY))) >= 0 ||
                            mbar_test(bar_full + 8 * (GU_FORCE % SLOTS), (GU_FORCE / SLOTS) & 1)) break;
                    mbar_wait(bar_full + 8 * (GU_UNIT % SLOTS), (GU_UNIT / SLOTS) & 1);
                    mbar_arrive(bar_go, 1);
                    uint32_t due = clock32() + WD_LAG;
#pragma unroll 1
                    for (int i = 0; i < 8; i++) {
#pragma unroll 1
                        for (int it = 0; it < SPIN_LIMIT; it++) if ((int)(clock32() - due) >= 0) break;
                        due += WD_PACE;
                        tma3d(sb + SM_WD + i * 2048, &p.m_wd, 0, 16 * ffn, i, bar_wd);
                    }
                }
            }
        } else {
            const uint32_t tag = lds32(sb + SM_ML + 8);
            if (warp == 9) {
                if (lane == 0) {
                    asm volatile("prefetch.tensormap [%0];" :: "l"(&p.m_wo) : "memory");
                    asm volatile("prefetch.tensormap [%0];" :: "l"(&p.m_wg) : "memory");
                    asm volatile("prefetch.tensormap [%0];" :: "l"(&p.m_wu) : "memory");
                    asm volatile("prefetch.tensormap [%0];" :: "l"(&p.m_wd) : "memory");
                    asm volatile("prefetch.tensormap [%0];" :: "l"(&p.m_v) : "memory");
                }
                if (cta == ZERO_CTA) {
                    mbar_wait(bar_trig, 0);
#pragma unroll 1
                    for (int i = 0; i < 16; i++) g_acc[acc_idx(32 * i + lane)] = make_float4(0.f, 0.f, 0.f, 0.f);
                    asm volatile("fence.acq_rel.gpu;" ::: "memory");
                    __syncwarp();
                    if (lane < 4) st_relaxed64(&g_zflag[lane], (unsigned long long)tag << 32);
                }
            } else if (warp == 10) {
                if (is_ffn) {
                    mbar_wait(bar_trig + 8, 0);
#pragma unroll 1
                    for (int i = 2 * lane; i < 256; i += 64) {
                        unsigned long long q[8]; int it = 0; bool ok;
                        do {
                            ok = true;
#pragma unroll
                            for (int k = 0; k < 4; k++) {
                                asm volatile("ld.relaxed.gpu.global.v2.u64 {%0,%1}, [%2];" : "=l"(q[2 * k]), "=l"(q[2 * k + 1]) : "l"(mod_ptr(512 + 256 * k + i)) : "memory");
                                ok = ok && has_tag(q[2 * k], tag) && has_tag(q[2 * k + 1], tag);
                            }
                        } while (!ok && ++it < SPIN_LIMIT);
#pragma unroll
                        for (int e = 0; e < 2; e++) {
                            sts32(sb + SM_TV + 16 * (i + e) + 4, (uint32_t)q[e]);
                            sts32(sb + SM_TV + 16 * (i + e) + 8, add2(ONE2, (uint32_t)q[4 + e]));
                            sts32(sb + SM_TV + 16 * (i + e) + 12, (uint32_t)q[2 + e]);
                            sts32(sb + SM_GB + 4 * (i + e), (uint32_t)q[6 + e]);
                        }
                    }
                }
                __syncwarp();
                if (lane == 0) {
                    mbar_arrive(bar_aux, 1);
                    if (cta == 0) g_epoch = tag;
                }
            } else {
                mbar_wait(bar_trig + 16, 0);
                const unsigned long long* sp = &g_stat[(head * 32 + lane) * 2];
                const unsigned long long* lp = &g_ls[head * 256 + lane];
                unsigned long long q0, q1, q2; uint32_t w[8]; int it = 0;
                while (true) {
                    bool ok = true;
                    q0 = ld_relaxed64(sp); q1 = ld_relaxed64(sp + 1);
#pragma unroll
                    for (int i = 0; i < 8; i++) { const unsigned long long v = ld_relaxed64(lp + 32 * i); w[i] = (uint32_t)v; ok = ok && has_tag(v, tag); }
                    asm volatile("ld.acquire.gpu.global.u64 %0, [%1];" : "=l"(q2) : "l"(g_zflag) : "memory");
                    if (__all_sync(0xffffffffu, ok && has_tag(q0, tag) && has_tag(q1, tag) && has_tag(q2, tag)) || ++it >= SPIN_LIMIT) break;
                    __nanosleep(500);
                }
                const float mi = __uint_as_float((uint32_t)q0);
                float m = mi;
#pragma unroll
                for (int o = 16; o > 0; o >>= 1) m = fmaxf(m, __shfl_xor_sync(0xffffffffu, m, o));
                float l = __uint_as_float((uint32_t)q1) * __expf(mi - m);
#pragma unroll
                for (int o = 16; o > 0; o >>= 1) l += __shfl_xor_sync(0xffffffffu, l, o);
                const float il = __fdividef(1.0f, l);
#pragma unroll
                for (int i = 0; i < 8; i++) {
                    const uint32_t pp = pack_bf16(__expf(bf_lo(w[i]) - m) * il, __expf(bf_hi(w[i]) - m) * il);
                    const uint32_t a = sb + SM_PL + (16 * (i * 4 + (lane >> 3)) + (lane & 7)) * 2;
                    sts16(a, pp); sts16(a + 16, pp >> 16);
                }
                __syncwarp();
                if (lane == 0) {
                    sts64f(sb + SM_ML, m, il);
                    mbar_arrive(bar_aux, 1);
                }
            }
            if (warp < 11 && is_ffn && lane == 0) {
                const CUtensorMap* m = warp == 9 ? &p.m_wg : &p.m_wu;
                const uint32_t dst = sb + SM_GU + (warp - 9) * 16384;
                mbar_expect_tx(bar_gu, 16384);
                mbar_wait(bar_go, 0);
                uint32_t due = clock32() + (warp - 9) * (GU_PACE / 2);
#pragma unroll 1
                for (int i = 0; i < 512 / GU_ROWS; i++) {
#pragma unroll 1
                    for (int it = 0; it < SPIN_LIMIT; it++) if ((int)(clock32() - due) >= 0) break;
                    due += GU_PACE;
                    tma2d(dst + i * (GU_ROWS * 32), m, 16 * ffn, GU_ROWS * i, bar_gu);
                }
            }
        }
    }
}

typedef CUresult (*EncodeFn)(CUtensorMap*, CUtensorMapDataType, cuuint32_t, void*, const cuuint64_t*, const cuuint64_t*,
                             const cuuint32_t*, const cuuint32_t*, CUtensorMapInterleave, CUtensorMapSwizzle,
                             CUtensorMapL2promotion, CUtensorMapFloatOOBfill);
static void encode2d(EncodeFn f, CUtensorMap* m, const void* ptr, int cols, int rows, int bc, int br, CUtensorMapSwizzle sw, CUtensorMapL2promotion pr) {
    cuuint64_t dim[2] = {(cuuint64_t)cols, (cuuint64_t)rows};
    cuuint64_t str[1] = {(cuuint64_t)cols * 2};
    cuuint32_t box[2] = {(cuuint32_t)bc, (cuuint32_t)br};
    cuuint32_t es[2] = {1, 1};
    f(m, CU_TENSOR_MAP_DATA_TYPE_BFLOAT16, 2, (void*)ptr, dim, str, box, es, CU_TENSOR_MAP_INTERLEAVE_NONE, sw,
      pr, CU_TENSOR_MAP_FLOAT_OOB_FILL_NONE);
}
static void encode3d(EncodeFn f, CUtensorMap* m, const void* ptr, int cols, int rows, int br, int bb) {
    cuuint64_t dim[3] = {64, (cuuint64_t)rows, (cuuint64_t)(cols / 64)};
    cuuint64_t str[2] = {(cuuint64_t)cols * 2, 128};
    cuuint32_t box[3] = {64, (cuuint32_t)br, (cuuint32_t)bb};
    cuuint32_t es[3] = {1, 1, 1};
    f(m, CU_TENSOR_MAP_DATA_TYPE_BFLOAT16, 3, (void*)ptr, dim, str, box, es, CU_TENSOR_MAP_INTERLEAVE_NONE, CU_TENSOR_MAP_SWIZZLE_128B,
      CU_TENSOR_MAP_L2_PROMOTION_L2_128B, CU_TENSOR_MAP_FLOAT_OOB_FILL_NONE);
}

extern "C" void kernel_launch(void* const* d_in, const int* in_sizes, int n_in, void* d_out, int out_size) {
    Params p;
    void* fn = nullptr;
    cudaDriverEntryPointQueryResult qr;
    cudaGetDriverEntryPoint("cuTensorMapEncodeTiled", &fn, cudaEnableDefault, &qr);
    EncodeFn enc = (EncodeFn)fn;
    encode2d(enc, &p.m_mod, d_in[10], 3072, 512, 24, 256, CU_TENSOR_MAP_SWIZZLE_NONE, CU_TENSOR_MAP_L2_PROMOTION_L2_128B);
    encode3d(enc, &p.m_wq, d_in[3], 4096, 512, 256, 2);
    encode3d(enc, &p.m_wo, d_in[4], 512, 4096, 128, 1);
    encode3d(enc, &p.m_wd, d_in[8], 512, 1376, 16, 1);
    encode2d(enc, &p.m_v, d_in[2], 128, 32 * 4096, 32, 128, CU_TENSOR_MAP_SWIZZLE_64B, CU_TENSOR_MAP_L2_PROMOTION_L2_256B);
    encode2d(enc, &p.m_wg, d_in[6], 1376, 512, 16, GU_ROWS, CU_TENSOR_MAP_SWIZZLE_32B, CU_TENSOR_MAP_L2_PROMOTION_L2_128B);
    encode2d(enc, &p.m_wu, d_in[7], 1376, 512, 16, GU_ROWS, CU_TENSOR_MAP_SWIZZLE_32B, CU_TENSOR_MAP_L2_PROMOTION_L2_128B);
    p.x = (const __nv_bfloat16*)d_in[0];
    p.k = (const __nv_bfloat16*)d_in[1];
    p.v = (const __nv_bfloat16*)d_in[2];
    p.wo = (const __nv_bfloat16*)d_in[4];
    p.c = (const __nv_bfloat16*)d_in[9];
    p.out = (__nv_bfloat16*)d_out;
    p.zero = 0;
    cudaFuncSetAttribute(fused_decode_kernel, cudaFuncAttributeMaxDynamicSharedMemorySize, SM_TOTAL);
    fused_decode_kernel<<<NCTA, NTHREADS, SM_TOTAL>>>(p);
}
```
